```python
import torch

def _softmax(x, axis=-1):
    return torch.softmax(x, dim=axis)
def _gelu(x):
    return torch.nn.functional.gelu(x, approximate="tanh")
def _silu(x):
    return torch.nn.functional.silu(x)
def _sigmoid(x):
    return torch.sigmoid(x)
def _layernorm(x, axis=-1, eps=1e-5):
    m = x.mean(dim=axis, keepdim=True)
    v = x.var(dim=axis, keepdim=True, unbiased=False)
    return (x - m) / torch.sqrt(v + eps)
def _scatter_add(tgt, idx, src, axis=0):
    return tgt.clone().index_add_(axis, idx, src)
def _segment_sum(src, seg, n):
    out = torch.zeros((n,) + src.shape[1:], dtype=src.dtype)
    return out.index_add_(0, seg, src)
def _pad(x, pw):
    flat = tuple(v for pair in reversed(pw) for v in pair)
    return torch.nn.functional.pad(x, flat)

kernel_name = 'sequential_preLN__ssm_conv_s4__glu_gated_glu__prompt'

def setup_inputs():

    _w = (lambda a: (lambda t: t.to(torch.bfloat16) if t.is_floating_point() else t)(torch.as_tensor(a)))
    def _A_setup():
        B, L, D, N = 1, 2048, 448, 256
        A_re = -(lambda _x: torch.exp(torch.as_tensor(_x)))((lambda *s: torch.randn(*s, dtype=torch.bfloat16) * 3.2)(D, N))
        A_im = torch.pi * (lambda *s: torch.randn(*s, dtype=torch.bfloat16) * 0.05)(D, N)
        B_re = (lambda *s: torch.randn(*s, dtype=torch.bfloat16) * 0.05)(D, N)
        B_im = (lambda *s: torch.randn(*s, dtype=torch.bfloat16) * 0.05)(D, N)
        C_re = (lambda *s: torch.randn(*s, dtype=torch.bfloat16) * 0.05)(D, N)
        C_im = (lambda *s: torch.randn(*s, dtype=torch.bfloat16) * 0.05)(D, N)
        log_dt = (lambda *s: torch.randn(*s, dtype=torch.bfloat16) * 0.05)(D) * 0.5 - 4.0
        Dskip = (lambda *s: torch.randn(*s, dtype=torch.bfloat16) * 0.05)(D)
        return {
            "u": _w((lambda *s: torch.randn(*s, dtype=torch.bfloat16) * 0.05)(B, L, D)),
            "A_re": _w(A_re),
            "A_im": _w(A_im),
            "B_re": _w(B_re),
            "B_im": _w(B_im),
            "C_re": _w(C_re),
            "C_im": _w(C_im),
            "log_dt": _w(log_dt),
            "Dskip": _w(Dskip),
        }
    _A_in = _A_setup()

    def _B_setup():
        B, S, D, F = 1, 2048, 448, 1792
        return {
            "x": _w((lambda *s: torch.randn(*s, dtype=torch.bfloat16) * 0.05)(B, S, D)),
            "w_gate": _w((lambda *s: torch.randn(*s, dtype=torch.bfloat16) * 0.05)(D, F)),
            "w_up": _w((lambda *s: torch.randn(*s, dtype=torch.bfloat16) * 0.05)(D, F)),
            "w_down": _w((lambda *s: torch.randn(*s, dtype=torch.bfloat16) * 0.05)(F, D)),
        }
    _B_in = _B_setup()

    return {
        "A_u": _A_in["u"],
        "A_A_re": _A_in["A_re"],
        "A_A_im": _A_in["A_im"],
        "A_B_re": _A_in["B_re"],
        "A_B_im": _A_in["B_im"],
        "A_C_re": _A_in["C_re"],
        "A_C_im": _A_in["C_im"],
        "A_log_dt": _A_in["log_dt"],
        "A_Dskip": _A_in["Dskip"],
        "B_x": _B_in["x"],
        "B_w_gate": _B_in["w_gate"],
        "B_w_up": _B_in["w_up"],
        "B_w_down": _B_in["w_down"],
    }

def reference(A_u, A_A_re, A_A_im, A_B_re, A_B_im, A_C_re, A_C_im, A_log_dt, A_Dskip, B_x, B_w_gate, B_w_up, B_w_down):
    def _A_ref(u, A_re, A_im, B_re, B_im, C_re, C_im, log_dt, Dskip):
        Bsz, L, D = u.shape
        dt = torch.exp(log_dt)[:, None]
        A = A_re + 1j * A_im
        Bc = B_re + 1j * B_im
        Cc = C_re + 1j * C_im
        logdA = dt * A
        dB = dt * Bc
        l = (lambda x, dt: x.to(dt))(torch.arange(L), A_re.dtype)
        P = torch.exp(logdA[:, :, None] * l[None, None, :])
        K = torch.einsum("dn,dnl,dn->dl", Cc, P, dB).real
        L2 = 2 * L
        Kp = _pad(K, ((0, 0), (0, L)))
        up = (lambda x, *d: x.permute(*d))(u, 0, 2, 1)
        up = _pad(up, ((0, 0), (0, 0), (0, L)))
        Kf = (lambda x, axes=(-2,-1): torch.fft.rfft2(x.float(), dim=axes))(Kp[:, None, :], axes=(-2, -1))
        Uf = (lambda x, axes=(-2,-1): torch.fft.rfft2(x.float(), dim=axes))(up[:, :, None, :], axes=(-2, -1))
        Yf = Uf * Kf[None, :, :, :]
        y = (lambda x, s, axes=(-2,-1): torch.fft.irfft2(x, s=s, dim=axes).to(torch.bfloat16))(Yf, (1, L2), axes=(-2, -1))[:, :, 0, :L]
        y = (lambda x, *d: x.permute(*d))(y, 0, 2, 1) + u * Dskip[None, None, :]
        return y

    def _B_ref(x, w_gate, w_up, w_down):
        g = torch.einsum("bsd,df->bsf", x, w_gate)
        u = torch.einsum("bsd,df->bsf", x, w_up)
        h = _sigmoid(g) * u
        return torch.einsum("bsf,fd->bsd", h, w_down)

    x = A_u
    h = x + _A_ref(_layernorm(x, axis=-1), A_A_re, A_A_im, A_B_re, A_B_im, A_C_re, A_C_im, A_log_dt, A_Dskip)
    h2 = h + _B_ref(_layernorm(h, axis=-1), B_w_gate, B_w_up, B_w_down)
    return h2
```

```cpp
#include <cuda_runtime.h>
#include <cuda_bf16.h>
#include <cuda_fp16.h>
#include <cuda.h>
#include <stdint.h>

typedef __nv_bfloat16 bf16;

constexpr int SEQ = 2048;
constexpr int DM  = 448;
constexpr int NM  = 256;
constexpr int FF  = 1792;

__device__ __align__(1024) bf16  g_uT[DM * SEQ];
__device__ __align__(1024) bf16  g_xT[DM * SEQ];
__device__ __align__(1024) bf16  g_hT[DM * SEQ];
__device__ __align__(1024) bf16  g_H[SEQ * FF];
__device__ __align__(1024) float g_cs[2 * FF];
#define TS_MIN(i)
#define TS_MAX(i)
#define TS_MINT(i)
#define TP(k, i)
#define TS_MAXT(i)

__device__ __forceinline__ uint32_t smem_u32(const void* p) { return (uint32_t)__cvta_generic_to_shared(p); }
__device__ __forceinline__ float bf16r(float v) { return __bfloat162float(__float2bfloat16_rn(v)); }
__device__ __forceinline__ float bflo(uint32_t w) { return __uint_as_float(w << 16); }
__device__ __forceinline__ float bfhi(uint32_t w) { return __uint_as_float(w & 0xffff0000u); }
__device__ __forceinline__ uint32_t pack_bf16(float lo, float hi) {
  uint32_t r; asm("cvt.rn.bf16x2.f32 %0, %1, %2;" : "=r"(r) : "f"(hi), "f"(lo)); return r;
}
__device__ __forceinline__ uint32_t pack_f16(float lo, float hi) {
  uint32_t r; asm("cvt.rn.f16x2.f32 %0, %1, %2;" : "=r"(r) : "f"(hi), "f"(lo)); return r;
}
__device__ __forceinline__ float ex2f(float x) { float r; asm("ex2.approx.ftz.f32 %0, %1;" : "=f"(r) : "f"(x)); return r; }
__device__ __forceinline__ void pdl_launch() { asm volatile("griddepcontrol.launch_dependents;"); }
__device__ __forceinline__ void pdl_wait() { asm volatile("griddepcontrol.wait;" ::: "memory"); }

__device__ __forceinline__ void mbar_init(uint32_t a, int c) { asm volatile("mbarrier.init.shared::cta.b64 [%0], %1;" ::"r"(a), "r"(c)); }
__device__ __forceinline__ void mbar_expect(uint32_t a, uint32_t bytes) {
  asm volatile("mbarrier.arrive.expect_tx.shared::cta.b64 _, [%0], %1;" ::"r"(a), "r"(bytes) : "memory");
}
__device__ __forceinline__ void mbar_arrive(uint32_t a) { asm volatile("mbarrier.arrive.shared::cta.b64 _, [%0];" ::"r"(a) : "memory"); }
__device__ __forceinline__ void mbar_arrive_cluster(uint32_t remote_a) {
  asm volatile("mbarrier.arrive.shared::cluster.b64 _, [%0];" ::"r"(remote_a) : "memory");
}
__device__ __forceinline__ void mbar_wait(uint32_t a, uint32_t ph) {
  uint32_t ok; int it = 0;
  do {
    asm volatile("{.reg .pred p; mbarrier.try_wait.parity.shared::cta.b64 p, [%1], %2; selp.u32 %0,1,0,p;}"
                 : "=r"(ok) : "r"(a), "r"(ph) : "memory");
  } while (!ok && ++it < (1 << 24));
}
__device__ __forceinline__ uint32_t mapa(uint32_t a, uint32_t rank) {
  uint32_t r; asm volatile("mapa.shared::cluster.u32 %0, %1, %2;" : "=r"(r) : "r"(a), "r"(rank)); return r;
}
__device__ __forceinline__ void cluster_arrive() { asm volatile("barrier.cluster.arrive.release.aligned;" ::: "memory"); }
__device__ __forceinline__ void cluster_wait() { asm volatile("barrier.cluster.wait.acquire.aligned;" ::: "memory"); }
__device__ __forceinline__ void fence_async() { asm volatile("fence.proxy.async.shared::cta;" ::: "memory"); }
__device__ __forceinline__ void named_bar(int id, int n) { asm volatile("bar.sync %0, %1;" ::"r"(id), "r"(n) : "memory"); }

__device__ __forceinline__ void tma2d(uint32_t dst, const CUtensorMap* tm, uint32_t bar, int c0, int c1) {
  asm volatile("cp.async.bulk.tensor.2d.shared::cluster.global.mbarrier::complete_tx::bytes [%0], [%1, {%3,%4}], [%2];"
               ::"r"(dst), "l"(tm), "r"(bar), "r"(c0), "r"(c1) : "memory");
}
__device__ __forceinline__ void tma3d(uint32_t dst, const CUtensorMap* tm, uint32_t bar, int c0, int c1, int c2) {
  asm volatile("cp.async.bulk.tensor.3d.shared::cluster.global.mbarrier::complete_tx::bytes [%0], [%1, {%3,%4,%5}], [%2];"
               ::"r"(dst), "l"(tm), "r"(bar), "r"(c0), "r"(c1), "r"(c2) : "memory");
}
__device__ __forceinline__ void tma3d_mc(uint32_t dst, const CUtensorMap* tm, uint32_t bar, int c0, int c1, int c2, uint16_t mask) {
  asm volatile("cp.async.bulk.tensor.3d.shared::cluster.global.mbarrier::complete_tx::bytes.multicast::cluster [%0], [%1, {%3,%4,%5}], [%2], %6;"
               ::"r"(dst), "l"(tm), "r"(bar), "r"(c0), "r"(c1), "r"(c2), "h"(mask) : "memory");
}
__device__ __forceinline__ void tma2d_store(const CUtensorMap* tm, uint32_t src, int c0, int c1) {
  asm volatile("cp.async.bulk.tensor.2d.global.shared::cta.bulk_group [%0, {%2,%3}], [%1];"
               ::"l"(tm), "r"(src), "r"(c0), "r"(c1) : "memory");
}
__device__ __forceinline__ void bulk_commit() { asm volatile("cp.async.bulk.commit_group;" ::: "memory"); }
template <int N> __device__ __forceinline__ void bulk_wait_read() { asm volatile("cp.async.bulk.wait_group.read %0;" ::"n"(N) : "memory"); }
template <int N> __device__ __forceinline__ void bulk_wait() { asm volatile("cp.async.bulk.wait_group %0;" ::"n"(N) : "memory"); }
__device__ __forceinline__ void prefetch_tm(const CUtensorMap* tm) { asm volatile("prefetch.tensormap [%0];" ::"l"(tm) : "memory"); }

__device__ __forceinline__ void wg_fence() { asm volatile("wgmma.fence.sync.aligned;" ::: "memory"); }
__device__ __forceinline__ void wg_commit() { asm volatile("wgmma.commit_group.sync.aligned;" ::: "memory"); }
template <int N> __device__ __forceinline__ void wg_wait() { asm volatile("wgmma.wait_group.sync.aligned %0;" ::"n"(N) : "memory"); }
__device__ __forceinline__ uint64_t mk_desc(uint32_t addr, uint32_t lbo, uint32_t sbo, uint32_t swz) {
  return (uint64_t)((addr & 0x3FFFF) >> 4) | ((uint64_t)(lbo >> 4) << 16) | ((uint64_t)(sbo >> 4) << 32) | ((uint64_t)swz << 62);
}
__device__ __forceinline__ void ldsm_x4(uint32_t a, uint32_t& r0, uint32_t& r1, uint32_t& r2, uint32_t& r3) {
  asm volatile("ldmatrix.sync.aligned.m8n8.x4.shared.b16 {%0,%1,%2,%3}, [%4];" : "=r"(r0), "=r"(r1), "=r"(r2), "=r"(r3) : "r"(a));
}
__device__ __forceinline__ void ldsm_x4_t(uint32_t a, uint32_t& r0, uint32_t& r1, uint32_t& r2, uint32_t& r3) {
  asm volatile("ldmatrix.sync.aligned.m8n8.x4.trans.shared.b16 {%0,%1,%2,%3}, [%4];" : "=r"(r0), "=r"(r1), "=r"(r2), "=r"(r3) : "r"(a));
}
__device__ __forceinline__ void ldsm_x2_t(uint32_t a, uint32_t& r0, uint32_t& r1) {
  asm volatile("ldmatrix.sync.aligned.m8n8.x2.trans.shared.b16 {%0,%1}, [%2];" : "=r"(r0), "=r"(r1) : "r"(a));
}
__device__ __forceinline__ void stsm_x4(uint32_t a, uint32_t r0, uint32_t r1, uint32_t r2, uint32_t r3) {
  asm volatile("stmatrix.sync.aligned.m8n8.x4.shared.b16 [%0], {%1,%2,%3,%4};" ::"r"(a), "r"(r0), "r"(r1), "r"(r2), "r"(r3) : "memory");
}
__device__ __forceinline__ void stsm_x2(uint32_t a, uint32_t r0, uint32_t r1) {
  asm volatile("stmatrix.sync.aligned.m8n8.x2.shared.b16 [%0], {%1,%2};" ::"r"(a), "r"(r0), "r"(r1) : "memory");
}
__device__ __forceinline__ uint32_t lds32(uint32_t a) { uint32_t r; asm volatile("ld.shared.u32 %0, [%1];" : "=r"(r) : "r"(a)); return r; }
__device__ __forceinline__ void mma_bf16(float (&c)[4], uint32_t a0, uint32_t a1, uint32_t a2, uint32_t a3, uint32_t b0, uint32_t b1) {
  asm volatile("mma.sync.aligned.m16n8k16.row.col.f32.bf16.bf16.f32 {%0,%1,%2,%3}, {%4,%5,%6,%7}, {%8,%9}, {%0,%1,%2,%3};"
               : "+f"(c[0]), "+f"(c[1]), "+f"(c[2]), "+f"(c[3]) : "r"(a0), "r"(a1), "r"(a2), "r"(a3), "r"(b0), "r"(b1));
}
__device__ __forceinline__ void mma_f16(float (&c)[4], uint32_t a0, uint32_t a1, uint32_t a2, uint32_t a3, uint32_t b0, uint32_t b1) {
  asm volatile("mma.sync.aligned.m16n8k16.row.col.f32.f16.f16.f32 {%0,%1,%2,%3}, {%4,%5,%6,%7}, {%8,%9}, {%0,%1,%2,%3};"
               : "+f"(c[0]), "+f"(c[1]), "+f"(c[2]), "+f"(c[3]) : "r"(a0), "r"(a1), "r"(a2), "r"(a3), "r"(b0), "r"(b1));
}
__device__ __forceinline__ void cp_async16(uint32_t dst, const void* src) {
  asm volatile("cp.async.cg.shared.global [%0], [%1], 16;" ::"r"(dst), "l"(src) : "memory");
}
__device__ __forceinline__ void cp_async_wait_all() { asm volatile("cp.async.wait_all;" ::: "memory"); }

__device__ unsigned int g_cnt[4];

constexpr int LN_PITCH = 912;
constexpr int LN_STAT  = 16 * LN_PITCH;
constexpr int LN_SMEM  = LN_STAT + 7 * 128;
__device__ __forceinline__ void ln1_load(const bf16* __restrict__ x, int tile, uint32_t sb) {
#pragma unroll
  for (int k = 0; k < 2; k++) {
    const int c = threadIdx.x + 512 * k;
    const int r = c / 56, ch = c - r * 56;
    if (c < 896) cp_async16(sb + r * LN_PITCH + ch * 16, x + (size_t)(tile * 16 + r) * DM + ch * 8);
  }
}
__device__ __forceinline__ void ln1_tile(int tile, unsigned char* sm, uint32_t sb) {
  const int lane = threadIdx.x & 31, w = threadIdx.x >> 5;
  const int g = lane >> 2, t = lane & 3;
#define TPW 0
  TP(0, 0);
  cp_async_wait_all();
  __syncthreads();
  TP(0, 1);
  if (w < 7) {
    float s1[4] = {0.f, 0.f, 0.f, 0.f}, qa[4] = {0.f, 0.f, 0.f, 0.f}, qb[4] = {0.f, 0.f, 0.f, 0.f};
    const uint32_t ad = sb + ((lane & 7) + 8 * ((lane >> 3) & 1)) * LN_PITCH + (lane >> 4) * 16 + w * 128;
#pragma unroll
    for (int k = 0; k < 4; k++) {
      uint32_t a0, a1, a2, a3;
      ldsm_x4(ad + k * 32, a0, a1, a2, a3);
      mma_bf16(s1, a0, a1, a2, a3, 0x3f803f80u, 0x3f803f80u);
      mma_bf16(qa, a0, a1, a2, a3, a0, a2);
      mma_bf16(qb, a0, a1, a2, a3, a1, a3);
    }
    if (t == (g >> 1)) {
      float2* st = reinterpret_cast<float2*>(sm + LN_STAT) + w * 16;
      st[g]     = make_float2(s1[0], (g & 1) ? qa[1] : qa[0]);
      st[g + 8] = make_float2(s1[2], (g & 1) ? qb[3] : qb[2]);
    }
  }
  __syncthreads();
  TP(0, 2);
  if (w < 14) {
    float mb[4], rd[4];
    {
      const float2* st = reinterpret_cast<const float2*>(sm + LN_STAT) + (lane & 15);
      float sx = 0.f, sy = 0.f;
#pragma unroll
      for (int i = 0; i < 7; i++) { const float2 p = st[16 * i]; sx += p.x; sy += p.y; }
      const float mean = sx * (1.0f / DM);
      const float var = fmaxf(sy * (1.0f / DM) - mean * mean, 0.f);
      const float m = bf16r(mean);
      const float r = __fdiv_rn(1.0f, bf16r(sqrtf(bf16r(bf16r(var) + 1e-5f))));
#pragma unroll
      for (int e = 0; e < 4; e++) {
        mb[e] = __shfl_sync(0xffffffffu, m, 4 * t + e);
        rd[e] = __shfl_sync(0xffffffffu, r, 4 * t + e);
      }
    }
    const int r8 = lane & 7;
    const int tok = 4 * (r8 >> 1) + (r8 & 1) + 2 * ((lane >> 3) & 1);
    const uint32_t ad = sb + tok * LN_PITCH + (w * 32 + (lane >> 4) * 8) * 2;
    const size_t go = (size_t)(w * 32 + g) * SEQ + tile * 16 + 4 * t;
#pragma unroll
    for (int k = 0; k < 2; k++) {
      uint32_t v[4];
      ldsm_x4_t(ad + k * 32, v[0], v[1], v[2], v[3]);
#pragma unroll
      for (int h = 0; h < 2; h++) {
        const uint32_t d0 = pack_bf16(bflo(v[2 * h]) - mb[0], bfhi(v[2 * h]) - mb[1]);
        const uint32_t d1 = pack_bf16(bflo(v[2 * h + 1]) - mb[2], bfhi(v[2 * h + 1]) - mb[3]);
        const size_t o = go + (size_t)(16 * k + 8 * h) * SEQ;
        *reinterpret_cast<uint2*>(g_uT + o) = make_uint2(pack_bf16(bflo(d0) * rd[0], bfhi(d0) * rd[1]), pack_bf16(bflo(d1) * rd[2], bfhi(d1) * rd[3]));
        *reinterpret_cast<uint2*>(g_xT + o) = make_uint2(v[2 * h], v[2 * h + 1]);
      }
    }
    TP(0, 3);
  }
#undef TPW
}

__device__ __forceinline__ void ln1_publish() {
  __syncwarp();
  if ((threadIdx.x & 31) == 0 && threadIdx.x < 14 * 32) {
    __threadfence();
    asm volatile("red.release.gpu.global.add.u32 [%0], 1;" ::"l"(&g_cnt[0]) : "memory");
  }
}

__device__ __forceinline__ void colsum_task(const bf16* __restrict__ wg, const bf16* __restrict__ wu, const bf16* __restrict__ wd,
                                            int b2, float* sf, int tid, int bar) {
  const int lane = tid & 31, w = tid >> 5;
  const int mat = b2 / 56, cg = b2 % 56;
  const bf16* W = mat ? wu : wg;
  const int r = tid >> 2, c = tid & 3;
  float acc[8];
#pragma unroll
  for (int i = 0; i < 8; i++) acc[i] = 0.f;
  if (tid < 112) {
    const char* p = reinterpret_cast<const char*>(wd) + (size_t)(b2 * 112 + tid) * 128;
    asm volatile("prefetch.global.L2 [%0];" ::"l"(p));
  }
#pragma unroll
  for (int h = 0; h < 2; h++) {
    uint4 v[7];
#pragma unroll
    for (int k = 0; k < 7; k++)
      v[k] = __ldg(reinterpret_cast<const uint4*>(W + (size_t)(r + 32 * (k + 7 * h)) * FF + cg * 32 + c * 8));
#pragma unroll
    for (int k = 0; k < 7; k++) {
      acc[0] += bflo(v[k].x); acc[1] += bfhi(v[k].x); acc[2] += bflo(v[k].y); acc[3] += bfhi(v[k].y);
      acc[4] += bflo(v[k].z); acc[5] += bfhi(v[k].z); acc[6] += bflo(v[k].w); acc[7] += bfhi(v[k].w);
    }
  }
#pragma unroll
  for (int i = 0; i < 8; i++) {
    acc[i] += __shfl_xor_sync(0xffffffffu, acc[i], 4);
    acc[i] += __shfl_xor_sync(0xffffffffu, acc[i], 8);
    acc[i] += __shfl_xor_sync(0xffffffffu, acc[i], 16);
  }
  if (lane < 4) {
#pragma unroll
    for (int i = 0; i < 8; i++) sf[w * 32 + lane * 8 + i] = acc[i];
  }
  named_bar(bar, 128);
  if (tid < 32) g_cs[mat * FF + cg * 32 + tid] = (sf[tid] + sf[32 + tid]) + (sf[64 + tid] + sf[96 + tid]);
  named_bar(bar, 128);
}
__device__ __forceinline__ void wgmma_n256_t11(float (&d)[128], uint64_t da, uint64_t db, int sc) {
  asm volatile("{\n.reg .pred p;\nsetp.ne.b32 p, %130, 0;\n"
    "wgmma.mma_async.sync.aligned.m64n256k16.f32.bf16.bf16 {%0, %1, %2, %3, %4, %5, %6, %7, %8, %9, %10, %11, %12, %13, %14, %15, %16, %17, %18, %19, %20, %21, %22, %23, %24, %25, %26, %27, %28, %29, %30, %31, %32, %33, %34, %35, %36, %37, %38, %39, %40, %41, %42, %43, %44, %45, %46, %47, %48, %49, %50, %51, %52, %53, %54, %55, %56, %57, %58, %59, %60, %61, %62, %63, %64, %65, %66, %67, %68, %69, %70, %71, %72, %73, %74, %75, %76, %77, %78, %79, %80, %81, %82, %83, %84, %85, %86, %87, %88, %89, %90, %91, %92, %93, %94, %95, %96, %97, %98, %99, %100, %101, %102, %103, %104, %105, %106, %107, %108, %109, %110, %111, %112, %113, %114, %115, %116, %117, %118, %119, %120, %121, %122, %123, %124, %125, %126, %127}, %128, %129, p, 1, 1, 1, 1;\n}\n"
    : "+f"(d[0]), "+f"(d[1]), "+f"(d[2]), "+f"(d[3]), "+f"(d[4]), "+f"(d[5]), "+f"(d[6]), "+f"(d[7]), "+f"(d[8]), "+f"(d[9]), "+f"(d[10]), "+f"(d[11]), "+f"(d[12]), "+f"(d[13]), "+f"(d[14]), "+f"(d[15]), "+f"(d[16]), "+f"(d[17]), "+f"(d[18]), "+f"(d[19]), "+f"(d[20]), "+f"(d[21]), "+f"(d[22]), "+f"(d[23]), "+f"(d[24]), "+f"(d[25]), "+f"(d[26]), "+f"(d[27]), "+f"(d[28]), "+f"(d[29]), "+f"(d[30]), "+f"(d[31]), "+f"(d[32]), "+f"(d[33]), "+f"(d[34]), "+f"(d[35]), "+f"(d[36]), "+f"(d[37]), "+f"(d[38]), "+f"(d[39]), "+f"(d[40]), "+f"(d[41]), "+f"(d[42]), "+f"(d[43]), "+f"(d[44]), "+f"(d[45]), "+f"(d[46]), "+f"(d[47]), "+f"(d[48]), "+f"(d[49]), "+f"(d[50]), "+f"(d[51]), "+f"(d[52]), "+f"(d[53]), "+f"(d[54]), "+f"(d[55]), "+f"(d[56]), "+f"(d[57]), "+f"(d[58]), "+f"(d[59]), "+f"(d[60]), "+f"(d[61]), "+f"(d[62]), "+f"(d[63]), "+f"(d[64]), "+f"(d[65]), "+f"(d[66]), "+f"(d[67]), "+f"(d[68]), "+f"(d[69]), "+f"(d[70]), "+f"(d[71]), "+f"(d[72]), "+f"(d[73]), "+f"(d[74]), "+f"(d[75]), "+f"(d[76]), "+f"(d[77]), "+f"(d[78]), "+f"(d[79]), "+f"(d[80]), "+f"(d[81]), "+f"(d[82]), "+f"(d[83]), "+f"(d[84]), "+f"(d[85]), "+f"(d[86]), "+f"(d[87]), "+f"(d[88]), "+f"(d[89]), "+f"(d[90]), "+f"(d[91]), "+f"(d[92]), "+f"(d[93]), "+f"(d[94]), "+f"(d[95]), "+f"(d[96]), "+f"(d[97]), "+f"(d[98]), "+f"(d[99]), "+f"(d[100]), "+f"(d[101]), "+f"(d[102]), "+f"(d[103]), "+f"(d[104]), "+f"(d[105]), "+f"(d[106]), "+f"(d[107]), "+f"(d[108]), "+f"(d[109]), "+f"(d[110]), "+f"(d[111]), "+f"(d[112]), "+f"(d[113]), "+f"(d[114]), "+f"(d[115]), "+f"(d[116]), "+f"(d[117]), "+f"(d[118]), "+f"(d[119]), "+f"(d[120]), "+f"(d[121]), "+f"(d[122]), "+f"(d[123]), "+f"(d[124]), "+f"(d[125]), "+f"(d[126]), "+f"(d[127])
    : "l"(da), "l"(db), "r"(sc));
}
__device__ __forceinline__ void wgmma_n192_t11(float (&d)[96], uint64_t da, uint64_t db, int sc) {
  asm volatile("{\n.reg .pred p;\nsetp.ne.b32 p, %98, 0;\n"
    "wgmma.mma_async.sync.aligned.m64n192k16.f32.bf16.bf16 {%0, %1, %2, %3, %4, %5, %6, %7, %8, %9, %10, %11, %12, %13, %14, %15, %16, %17, %18, %19, %20, %21, %22, %23, %24, %25, %26, %27, %28, %29, %30, %31, %32, %33, %34, %35, %36, %37, %38, %39, %40, %41, %42, %43, %44, %45, %46, %47, %48, %49, %50, %51, %52, %53, %54, %55, %56, %57, %58, %59, %60, %61, %62, %63, %64, %65, %66, %67, %68, %69, %70, %71, %72, %73, %74, %75, %76, %77, %78, %79, %80, %81, %82, %83, %84, %85, %86, %87, %88, %89, %90, %91, %92, %93, %94, %95}, %96, %97, p, 1, 1, 1, 1;\n}\n"
    : "+f"(d[0]), "+f"(d[1]), "+f"(d[2]), "+f"(d[3]), "+f"(d[4]), "+f"(d[5]), "+f"(d[6]), "+f"(d[7]), "+f"(d[8]), "+f"(d[9]), "+f"(d[10]), "+f"(d[11]), "+f"(d[12]), "+f"(d[13]), "+f"(d[14]), "+f"(d[15]), "+f"(d[16]), "+f"(d[17]), "+f"(d[18]), "+f"(d[19]), "+f"(d[20]), "+f"(d[21]), "+f"(d[22]), "+f"(d[23]), "+f"(d[24]), "+f"(d[25]), "+f"(d[26]), "+f"(d[27]), "+f"(d[28]), "+f"(d[29]), "+f"(d[30]), "+f"(d[31]), "+f"(d[32]), "+f"(d[33]), "+f"(d[34]), "+f"(d[35]), "+f"(d[36]), "+f"(d[37]), "+f"(d[38]), "+f"(d[39]), "+f"(d[40]), "+f"(d[41]), "+f"(d[42]), "+f"(d[43]), "+f"(d[44]), "+f"(d[45]), "+f"(d[46]), "+f"(d[47]), "+f"(d[48]), "+f"(d[49]), "+f"(d[50]), "+f"(d[51]), "+f"(d[52]), "+f"(d[53]), "+f"(d[54]), "+f"(d[55]), "+f"(d[56]), "+f"(d[57]), "+f"(d[58]), "+f"(d[59]), "+f"(d[60]), "+f"(d[61]), "+f"(d[62]), "+f"(d[63]), "+f"(d[64]), "+f"(d[65]), "+f"(d[66]), "+f"(d[67]), "+f"(d[68]), "+f"(d[69]), "+f"(d[70]), "+f"(d[71]), "+f"(d[72]), "+f"(d[73]), "+f"(d[74]), "+f"(d[75]), "+f"(d[76]), "+f"(d[77]), "+f"(d[78]), "+f"(d[79]), "+f"(d[80]), "+f"(d[81]), "+f"(d[82]), "+f"(d[83]), "+f"(d[84]), "+f"(d[85]), "+f"(d[86]), "+f"(d[87]), "+f"(d[88]), "+f"(d[89]), "+f"(d[90]), "+f"(d[91]), "+f"(d[92]), "+f"(d[93]), "+f"(d[94]), "+f"(d[95])
    : "l"(da), "l"(db), "r"(sc));
}
__device__ __forceinline__ void wgmma_n112_t01(float (&d)[56], uint64_t da, uint64_t db, int sc) {
  asm volatile("{\n.reg .pred p;\nsetp.ne.b32 p, %58, 0;\n"
    "wgmma.mma_async.sync.aligned.m64n112k16.f32.bf16.bf16 {%0, %1, %2, %3, %4, %5, %6, %7, %8, %9, %10, %11, %12, %13, %14, %15, %16, %17, %18, %19, %20, %21, %22, %23, %24, %25, %26, %27, %28, %29, %30, %31, %32, %33, %34, %35, %36, %37, %38, %39, %40, %41, %42, %43, %44, %45, %46, %47, %48, %49, %50, %51, %52, %53, %54, %55}, %56, %57, p, 1, 1, 0, 1;\n}\n"
    : "+f"(d[0]), "+f"(d[1]), "+f"(d[2]), "+f"(d[3]), "+f"(d[4]), "+f"(d[5]), "+f"(d[6]), "+f"(d[7]), "+f"(d[8]), "+f"(d[9]), "+f"(d[10]), "+f"(d[11]), "+f"(d[12]), "+f"(d[13]), "+f"(d[14]), "+f"(d[15]), "+f"(d[16]), "+f"(d[17]), "+f"(d[18]), "+f"(d[19]), "+f"(d[20]), "+f"(d[21]), "+f"(d[22]), "+f"(d[23]), "+f"(d[24]), "+f"(d[25]), "+f"(d[26]), "+f"(d[27]), "+f"(d[28]), "+f"(d[29]), "+f"(d[30]), "+f"(d[31]), "+f"(d[32]), "+f"(d[33]), "+f"(d[34]), "+f"(d[35]), "+f"(d[36]), "+f"(d[37]), "+f"(d[38]), "+f"(d[39]), "+f"(d[40]), "+f"(d[41]), "+f"(d[42]), "+f"(d[43]), "+f"(d[44]), "+f"(d[45]), "+f"(d[46]), "+f"(d[47]), "+f"(d[48]), "+f"(d[49]), "+f"(d[50]), "+f"(d[51]), "+f"(d[52]), "+f"(d[53]), "+f"(d[54]), "+f"(d[55])
    : "l"(da), "l"(db), "r"(sc));
}

struct cplx { float re, im; };
__device__ __forceinline__ cplx cmul(cplx a, cplx b) {
  cplx r; r.re = a.re * b.re - a.im * b.im; r.im = a.re * b.im + a.im * b.re; return r;
}
__device__ __forceinline__ cplx zpow_acc(float a2, float bt, float c) {
  float mag = ex2f(a2 * c);
  float tr = bt * c;
  tr -= rintf(tr);
  float ang = tr * 6.283185307179586f;
  cplx r; r.re = mag * __cosf(ang); r.im = mag * __sinf(ang); return r;
}

constexpr int SB_TAB  = 0;
constexpr int SB_WREG = 7168;
constexpr int UZ = 40;
constexpr int SB_U    = 4 * SB_WREG;
constexpr int SB_X    = SB_U + 172 * 36;
constexpr int SB_KV   = SB_X + 4096;
constexpr int SB_TOTAL = (SB_KV + 644 * 4 + 127) / 128 * 128;
constexpr int SB_F3   = 0;
constexpr int SB_F2   = 1792;
constexpr int SB_Y    = 4096;
constexpr int SB_KD   = SB_Y;
constexpr int SB_KDO  = SB_KD + 2240;
constexpr int FR_LN = 4 * SB_TOTAL;
constexpr int FRONT_SMEM = FR_LN + LN_SMEM;

__device__ __forceinline__ int rowaddr(int r) { return 32 * r + 16 * (r >> 2); }
__device__ __forceinline__ void gen8(unsigned char* p, cplx s, cplx r1, cplx r1sq, cplx r2) {
  cplx v[8];
  v[0] = s; v[1] = cmul(s, r1); v[2] = cmul(s, r1sq); v[3] = cmul(v[1], r1sq);
#pragma unroll
  for (int j = 0; j < 4; j++) v[4 + j] = cmul(v[j], r2);
  uint4 a, b;
  a.x = pack_f16(v[0].re, v[1].re); a.y = pack_f16(v[2].re, v[3].re); a.z = pack_f16(v[4].re, v[5].re); a.w = pack_f16(v[6].re, v[7].re);
  b.x = pack_f16(v[0].im, v[1].im); b.y = pack_f16(v[2].im, v[3].im); b.z = pack_f16(v[4].im, v[5].im); b.w = pack_f16(v[6].im, v[7].im);
  *reinterpret_cast<uint4*>(p) = a;
  *reinterpret_cast<uint4*>(p + 8 * 112) = b;
}
__device__ __forceinline__ cplx csq(cplx a) { cplx r; r.re = a.re * a.re - a.im * a.im; r.im = 2.f * a.re * a.im; return r; }
__device__ __forceinline__ cplx cconj(cplx a) { a.im = -a.im; return a; }
__device__ __forceinline__ uint2 lds64(uint32_t a) { uint2 r; asm volatile("ld.shared.v2.u32 {%0,%1}, [%2];" : "=r"(r.x), "=r"(r.y) : "r"(a)); return r; }

__global__ void __launch_bounds__(512, 1) k_ssm(const bf16* __restrict__ Are, const bf16* __restrict__ Aim,
                                             const bf16* __restrict__ Bre, const bf16* __restrict__ Bim,
                                             const bf16* __restrict__ Cre, const bf16* __restrict__ Cim,
                                             const bf16* __restrict__ log_dt, const bf16* __restrict__ Dskip,
                                             const bf16* __restrict__ x, const bf16* __restrict__ wg,
                                             const bf16* __restrict__ wu, const bf16* __restrict__ wd) {
  pdl_launch();
  TS_MIN(0); TS_MAX(1);
#define TPW 1
  TP(1, 0);
  extern __shared__ __align__(1024) unsigned char smem_all[];
  const int sub = threadIdx.x >> 7;
  const int tid = threadIdx.x & 127, lane = tid & 31;
  const int bar = 1 + sub;
  unsigned char* sm = smem_all + sub * SB_TOTAL;
  const uint32_t sbase = smem_u32(sm);
  const int w = ((tid >> 5) + sub) & 3;
  const int g = lane >> 2, t = lane & 3;
  const bool do_ln = blockIdx.x < 128;
  if (do_ln) ln1_load(x, blockIdx.x, smem_u32(smem_all + FR_LN));
  if (blockIdx.x >= 112) {
    if (do_ln) { ln1_tile(blockIdx.x, smem_all + FR_LN, smem_u32(smem_all + FR_LN)); ln1_publish(); }
    for (int task = (blockIdx.x - 112) * 4 + sub; task < 112; task += 80)
      colsum_task(wg, wu, wd, task, reinterpret_cast<float*>(sm + SB_X), tid, bar);
    return;
  }
  const int d = blockIdx.x * 4 + sub;
  const int pidx = (d * NM + 64 * w) / 2 + lane;
  const uint32_t pAre = __ldg(reinterpret_cast<const uint32_t*>(Are) + pidx), pAim = __ldg(reinterpret_cast<const uint32_t*>(Aim) + pidx);
  const uint32_t pBre = __ldg(reinterpret_cast<const uint32_t*>(Bre) + pidx), pBim = __ldg(reinterpret_cast<const uint32_t*>(Bim) + pidx);
  const uint32_t pCre = __ldg(reinterpret_cast<const uint32_t*>(Cre) + pidx), pCim = __ldg(reinterpret_cast<const uint32_t*>(Cim) + pidx);
  const float dt = bf16r(expf(__bfloat162float(log_dt[d])));
  const uint32_t dsk2 = (uint32_t)__bfloat16_as_ushort(Dskip[d]) * 0x10001u;
  ln1_tile(blockIdx.x, smem_all + FR_LN, smem_u32(smem_all + FR_LN));
  TS_MIN(2); TS_MAX(3);
  if (tid < 90) *reinterpret_cast<uint4*>(sm + SB_U + tid * 16) = make_uint4(0, 0, 0, 0);
  if (tid >= 96 && tid < 105) *reinterpret_cast<uint4*>(sm + SB_U + 168 * 36 + (tid - 96) * 16) = make_uint4(0, 0, 0, 0);
  float w0re, w0im, w1re, w1im;
  {
    const float br0 = dt * bflo(pBre), bi0 = dt * bflo(pBim), br1 = dt * bfhi(pBre), bi1 = dt * bfhi(pBim);
    w0re = bflo(pCre) * br0 - bflo(pCim) * bi0; w0im = bflo(pCre) * bi0 + bflo(pCim) * br0;
    w1re = bfhi(pCre) * br1 - bfhi(pCim) * bi1; w1im = bfhi(pCre) * bi1 + bfhi(pCim) * br1;
  }
  float mx = fmaxf(fmaxf(fabsf(w0re), fabsf(w0im)), fmaxf(fabsf(w1re), fabsf(w1im)));
#pragma unroll
  for (int o = 16; o > 0; o >>= 1) mx = fmaxf(mx, __shfl_xor_sync(0xffffffffu, mx, o));
  int ex = (__float_as_uint(mx) >> 23) & 0xff;
  ex = min(max(ex, 1), 252);
  const float scale = __uint_as_float((uint32_t)(253 - ex) << 23);
  const float inv_scale = __uint_as_float((uint32_t)(ex + 1) << 23);

  TP(1, 1);
  float acc[5][4];
#pragma unroll
  for (int i = 0; i < 5; i++) { acc[i][0] = acc[i][1] = acc[i][2] = acc[i][3] = 0.f; }
  float k2048 = 0.f;
  unsigned char* tabw = sm + SB_TAB + w * SB_WREG;
  const uint32_t ldA = sbase + SB_TAB + w * SB_WREG + ((lane & 7) + 8 * ((lane >> 4) & 1)) * 112 + ((lane >> 3) & 1) * 16;
  const uint32_t ldB = sbase + SB_TAB + w * SB_WREG + ((lane & 7) + 8 * ((lane >> 3) & 1)) * 112 + 32 + (lane >> 4) * 16;
#pragma unroll 1
  for (int r = 0; r < 2; r++) {
    {
      const float a2 = dt * (r ? bfhi(pAre) : bflo(pAre)) * 1.4426950408889634f;
      const float bt = dt * (r ? bfhi(pAim) : bflo(pAim)) * 0.15915494309189535f;
      cplx W; W.re = (r ? w1re : w0re) * scale; W.im = -(r ? w1im : w0im) * scale;
      unsigned char* rec = tabw + ((lane >> 3) * 16 + (lane & 7)) * 112;
      const cplx y1 = zpow_acc(a2, -bt, 1.f), z8 = zpow_acc(a2, bt, 8.f), y128 = zpow_acc(a2, -bt, 128.f);
      const cplx y512 = zpow_acc(a2, -bt, 512.f), y1024 = zpow_acc(a2, -bt, 1024.f);
      const cplx z16 = csq(z8), z32 = csq(z16), z64 = csq(z32);
      const cplx y2 = csq(y1), y4 = csq(y2), y256 = csq(y128);
      cplx one; one.re = 1.f; one.im = 0.f;
      gen8(rec, one, z8, z16, z32);
      gen8(rec + 16, z64, z8, z16, z32);
      gen8(rec + 32, W, y1, y2, y4);
      gen8(rec + 48, cmul(W, y128), y1, y2, y4);
      gen8(rec + 64, cmul(W, y256), y2, y4, y128);
      gen8(rec + 80, cmul(W, y512), y128, y256, y4);
      const cplx w1024 = cmul(W, y1024);
      gen8(rec + 96, w1024, y128, y256, y512);
      k2048 += w1024.re * y1024.re - w1024.im * y1024.im;
    }
    if (r == 0) ln1_publish();
    __syncwarp();
#pragma unroll
    for (int ks = 0; ks < 4; ks++) {
      uint32_t a0, a1, a2, a3, b0, b1, b2, b3;
      ldsm_x4_t(ldA + ks * 1792, a0, a1, a2, a3);
      ldsm_x4_t(ldB + ks * 1792, b0, b1, b2, b3);
      mma_f16(acc[0], a0, a1, a2, a3, b0, b1);
      mma_f16(acc[1], a0, a1, a2, a3, b2, b3);
      ldsm_x4_t(ldB + ks * 1792 + 32, b0, b1, b2, b3);
      mma_f16(acc[2], a0, a1, a2, a3, b0, b1);
      mma_f16(acc[3], a0, a1, a2, a3, b2, b3);
      ldsm_x2_t(ldB + ks * 1792 + 64, b0, b1);
      mma_f16(acc[4], a0, a1, a2, a3, b0, b1);
    }
    __syncwarp();
  }
  TP(1, 2);
  {
    float* red = reinterpret_cast<float*>(tabw);
#pragma unroll
    for (int hr = 0; hr < 2; hr++) {
      const int row = g + 8 * hr;
      *reinterpret_cast<float2*>(red + 8 * row + 2 * t) = make_float2(acc[0][2 * hr] * inv_scale, acc[0][2 * hr + 1] * inv_scale);
      *reinterpret_cast<float2*>(red + 128 + 8 * row + 2 * t) = make_float2(acc[1][2 * hr] * inv_scale, acc[1][2 * hr + 1] * inv_scale);
      *reinterpret_cast<float2*>(red + 256 + 64 * (t >> 1) + 2 * (t & 1) + 4 * row) = make_float2(acc[2][2 * hr] * inv_scale, acc[2][2 * hr + 1] * inv_scale);
      red[384 + 64 * (t & 1) + (t >> 1) + 2 * row] = acc[3][2 * hr] * inv_scale;
      red[384 + 64 * (t & 1) + 32 + (t >> 1) + 2 * row] = acc[3][2 * hr + 1] * inv_scale;
      red[512 + 32 * t + row] = acc[4][2 * hr] * inv_scale;
      red[512 + 32 * t + 16 + row] = acc[4][2 * hr + 1] * inv_scale;
    }
#pragma unroll
    for (int o = 16; o > 0; o >>= 1) k2048 += __shfl_xor_sync(0xffffffffu, k2048, o);
    if (lane == 0) red[640] = k2048 * inv_scale;
  }
  named_bar(bar, 128);
  float* Kv = reinterpret_cast<float*>(sm + SB_KV);
  {
    const float* r0 = reinterpret_cast<const float*>(sm + SB_TAB);
    constexpr int WS = SB_WREG / 4;
    const float4 a = *reinterpret_cast<const float4*>(r0 + 4 * tid), b = *reinterpret_cast<const float4*>(r0 + WS + 4 * tid);
    const float4 c = *reinterpret_cast<const float4*>(r0 + 2 * WS + 4 * tid), e = *reinterpret_cast<const float4*>(r0 + 3 * WS + 4 * tid);
    *reinterpret_cast<float4*>(Kv + 4 * tid) =
        make_float4((a.x + b.x) + (c.x + e.x), (a.y + b.y) + (c.y + e.y), (a.z + b.z) + (c.z + e.z), (a.w + b.w) + (c.w + e.w));
    const int i = 512 + tid;
    Kv[i] = (r0[i] + r0[WS + i]) + (r0[2 * WS + i] + r0[3 * WS + i]);
    if (tid == 0) Kv[640] = (r0[640] + r0[WS + 640]) + (r0[2 * WS + 640] + r0[3 * WS + 640]);
  }
  named_bar(bar, 128);
  TP(1, 4);
  {
    uint32_t* ee = reinterpret_cast<uint32_t*>(sm + SB_KD);
#pragma unroll
    for (int it = 0; it < 3; it++) {
      const int x = tid + 128 * it;
      if (it < 2 || tid < 32) {
        const int j = 528 - 2 * x, m = (j >> 1) - 1;
        const int ie = j < 256 ? j : 128 + (j >> 1);
        const int io = j <= 256 ? j - 1 : 128 + m + (m & 1);
        float k1 = (j >= 0 && j <= 510) ? Kv[ie] : 0.f;
        const float k2 = (j >= 1 && j <= 510) ? Kv[io] : 0.f;
        if (j == 510) k1 -= Kv[384];
        float k0 = __shfl_up_sync(0xffffffffu, k2, 1);
        if (lane == 0) { const int m1 = m + 1; k0 = (j >= -1 && j <= 508) ? Kv[j < 256 ? j + 1 : 128 + m1 + (m1 & 1)] : 0.f; }
        const uint32_t we = pack_bf16(k1, k2), wo = pack_bf16(k0, k1);
        if (x < 272) {
          ee[2 * x] = we; ee[560 + 2 * x] = wo;
          if (x >= 4) { ee[2 * x - 7] = we; ee[560 + 2 * x - 7] = wo; }
        }
      }
    }
    if (tid < 96) {
      const int f = tid >= 48, x = tid - 48 * f;
      const int j = 144 - 2 * x;
      const float* F = Kv + 384 + f;
      const int hi = 128 - f;
      const float k0 = (j + 1 >= 64 && j + 1 <= hi) ? F[2 * j + 2] : 0.f, k1 = (j >= 64 && j <= hi) ? F[2 * j] : 0.f;
      const float k2 = (j - 1 >= 64 && j - 1 <= hi) ? F[2 * j - 2] : 0.f;
      const uint32_t we = pack_bf16(k1, k2), wo = pack_bf16(k0, k1);
      uint32_t* p = reinterpret_cast<uint32_t*>(sm + SB_F3) + f * 224;
      p[2 * x] = we; p[112 + 2 * x] = wo;
      if (x < 44) { p[2 * x + 9] = we; p[112 + 2 * x + 9] = wo; }
    }
    {
      const int f = tid >> 6, x = tid & 63;
      const int j = 160 - 2 * x;
      const float* F = Kv + 256 + f;
      const float k0 = (j + 1 >= 64 && j + 1 <= 127) ? F[2 * j + 2] : 0.f, k1 = (j >= 64 && j <= 127) ? F[2 * j] : 0.f;
      const float k2 = (j - 1 >= 64 && j - 1 <= 127) ? F[2 * j - 2] : 0.f;
      const uint32_t we = pack_bf16(k1, k2), wo = pack_bf16(k0, k1);
      uint32_t* p = reinterpret_cast<uint32_t*>(sm + SB_F2) + f * 288;
      p[2 * x] = we; p[144 + 2 * x] = wo;
      p[2 * x + 17] = we; p[144 + 2 * x + 17] = wo;
    }
  }
  const float k1024 = Kv[512];
  TS_MIN(4); TS_MAX(5);
  if (lane == 0) {
    unsigned int v; int it = 0;
    do { asm volatile("ld.acquire.gpu.global.u32 %0, [%1];" : "=r"(v) : "l"(&g_cnt[0]) : "memory"); } while (v < 128u * 14u && ++it < (1 << 22));
  }
  __syncwarp();
  TS_MIN(6); TS_MAX(7);
  TP(1, 3);
#pragma unroll
  for (int k = 0; k < 2; k++) {
    const int ch = tid + 128 * k;
    cp_async16(sbase + SB_U + rowaddr((ch >> 1) + UZ) + (ch & 1) * 16, g_uT + (size_t)d * SEQ + ch * 8);
    cp_async16(sbase + SB_X + ch * 16, g_xT + (size_t)d * SEQ + ch * 8);
  }
  cp_async_wait_all();
  named_bar(bar, 128);
  TP(1, 5);
  const int krow = (lane & 7) + 8 * ((lane >> 3) & 1);
  if (w < 2) {
    float acd[4][2][4];
#pragma unroll
    for (int c = 0; c < 4; c++)
#pragma unroll
      for (int i = 0; i < 2; i++)
#pragma unroll
        for (int e = 0; e < 4; e++) acd[c][i][e] = 0.f;
    const uint32_t aQ = sbase + SB_U + rowaddr(UZ + 64 * w + 4 * krow) + (lane >> 4) * 16;
    const uint32_t pb = sbase + ((g & 1) ? SB_KDO + ((529 - g) / 2 + t) * 8 : SB_KD + ((528 - g) / 2 + t) * 8);
    uint32_t Q[36][4];
#define QOFF(j) (32 * (j) + 16 * (((j) + 64) / 4 - 16))
#pragma unroll
    for (int n = 0; n < 5; n++) ldsm_x4(aQ + QOFF(3 - n), Q[n][0], Q[n][1], Q[n][2], Q[n][3]);
#pragma unroll
    for (int q = 0; q < 33; q++) {
      if (q + 5 < 36) ldsm_x4(aQ + QOFF(3 - (q + 5)), Q[q + 5][0], Q[q + 5][1], Q[q + 5][2], Q[q + 5][3]);
      const uint2 e0 = lds64(pb - 32 * (2 * q));
      const uint2 e1 = lds64(pb - 32 * (2 * q + 1));
#pragma unroll
      for (int c = 0; c < 4; c++) {
        mma_bf16(acd[c][0], Q[3 - c + q][0], Q[3 - c + q][1], Q[3 - c + q][2], Q[3 - c + q][3], e0.x, e0.y);
        mma_bf16(acd[c][1], Q[3 - c + q][0], Q[3 - c + q][1], Q[3 - c + q][2], Q[3 - c + q][3], e1.x, e1.y);
      }
    }
#undef QOFF
    const int yl = (64 * (16 * w + g) + 2 * t + 16 * (g & 1) + 8 * ((g >> 1) & 1)) * 4;
    unsigned char* yb = sm + SB_Y + 8192;
#pragma unroll
    for (int c = 0; c < 4; c++)
#pragma unroll
      for (int nu = 0; nu < 2; nu++)
#pragma unroll
        for (int hr = 0; hr < 2; hr++)
          *reinterpret_cast<float2*>(yb + ((yl ^ ((16 * c + 8 * (nu ^ (c >> 1))) * 4)) + hr * 2048)) = make_float2(acd[c][nu][2 * hr], acd[c][nu][2 * hr + 1]);
  } else {
    const int yl = (16 * (g ^ ((g >> 2) & 1)) + 2 * t + 8 * ((g >> 1) & 1)) * 4;
    if (w == 2) {
      float ac[7][2][4];
#pragma unroll
      for (int T = 0; T < 7; T++)
#pragma unroll
        for (int i = 0; i < 2; i++)
#pragma unroll
          for (int e = 0; e < 4; e++) ac[T][i][e] = 0.f;
      uint32_t BA[2][4];
#pragma unroll
      for (int ks = 0; ks < 2; ks++)
#pragma unroll
        for (int r = 0; r < 4; r++) {
          uint32_t v = 0;
#pragma unroll
          for (int e = 0; e < 2; e++) {
            const int dlt = (2 * t + e + 8 * (r >> 1) + 16 * ks - 8) - g;
            const bool on = (r & 1) ? (dlt >= -5 && dlt <= -3) : (dlt >= -2 && dlt <= 2);
            v |= on ? (0x3f80u << (16 * e)) : 0u;
          }
          BA[ks][r] = v;
        }
      const int chl = 2 * UZ + (lane & 7) + (lane >> 3) - 1;
      const uint32_t ub = sbase + SB_U + rowaddr(chl >> 1) + (chl & 1) * 16;
      const uint32_t fb = sbase + SB_F2 + (80 - (g - t)) * 8;
#pragma unroll 1
      for (int f = 0; f < 2; f++) {
#pragma unroll
        for (int sp = 0; sp < 2; sp++) {
          uint2 A01[2][3], A23[2][3];
#pragma unroll
          for (int k = 0; k < 3; k++)
#pragma unroll
            for (int nu = 0; nu < 2; nu++) {
              A01[nu][k] = lds64(fb + f * 1152 + nu * 576 - 32 * (6 + 2 * (2 * k + sp)));
              A23[nu][k] = lds64(fb + f * 1152 + nu * 576 - 32 * (5 + 2 * (2 * k + sp)));
            }
#pragma unroll
          for (int beta = 11 - sp; beta >= -1; beta -= 2) {
            uint32_t bb[2];
#pragma unroll
            for (int o = 0; o < 2; o++) {
              uint32_t u0, u1, u2, u3;
              ldsm_x4(ub + (2 * beta + o) * 144, u0, u1, u2, u3);
              float z[4] = {0.f, 0.f, 0.f, 0.f};
              mma_bf16(z, BA[0][0], BA[0][1], BA[0][2], BA[0][3], u0, u1);
              mma_bf16(z, BA[1][0], BA[1][1], BA[1][2], BA[1][3], u2, u3);
              bb[o] = f ? pack_bf16(z[2], z[3]) : pack_bf16(z[0], z[1]);
            }
#pragma unroll
            for (int k = 0; k < 3; k++) {
              const int T = (beta + 3 + 2 * k + sp) / 2;
              if (T <= 7) {
                mma_bf16(ac[T - 1][0], A01[0][k].x, A01[0][k].y, A23[0][k].x, A23[0][k].y, bb[0], bb[1]);
                mma_bf16(ac[T - 1][1], A01[1][k].x, A01[1][k].y, A23[1][k].x, A23[1][k].y, bb[0], bb[1]);
              }
            }
          }
        }
      }
      named_bar(5 + bar, 96);
      unsigned char* yb = sm + SB_Y;
#pragma unroll
      for (int T = 0; T <= 7; T++)
#pragma unroll
        for (int nu = 0; nu < 2; nu++)
#pragma unroll
          for (int hr = 0; hr < 2; hr++)
            *reinterpret_cast<float2*>(yb + ((yl ^ ((8 * (nu ^ hr)) * 4)) + (16 * T + 8 * hr) * 64)) =
                T ? make_float2(ac[T ? T - 1 : 0][nu][2 * hr], ac[T ? T - 1 : 0][nu][2 * hr + 1]) : make_float2(0.f, 0.f);
    } else {
      float ac[5][2][4];
#pragma unroll
      for (int T = 0; T < 5; T++)
#pragma unroll
        for (int i = 0; i < 2; i++)
#pragma unroll
          for (int e = 0; e < 4; e++) ac[T][i][e] = 0.f;
      const uint32_t fb = sbase + SB_F3 + ((g & 1) ? 448 + ((145 - g) / 2 + t) * 8 : ((144 - g) / 2 + t) * 8);
      uint32_t ur[3];
#pragma unroll
      for (int sg = 0; sg < 3; sg++) ur[sg] = sbase + SB_U + rowaddr(UZ + (lane & 7) + 8 * (lane >> 4) + sg - 1) + ((lane >> 3) & 1) * 16;
#pragma unroll 1
      for (int f = 0; f < 2; f++) {
        uint32_t BA[3][4];
        const int lo = f ? -11 : -4, hi = f ? -5 : 4;
#pragma unroll
        for (int sg = 0; sg < 3; sg++)
#pragma unroll
          for (int r = 0; r < 4; r++) {
            uint32_t v = 0;
#pragma unroll
            for (int e = 0; e < 2; e++) {
              const int dlt = (2 * t + e + 8 * (r >> 1) + 16 * (sg - 1)) - (g + 8 * (r & 1));
              v |= (dlt >= lo && dlt <= hi) ? (0x3f80u << (16 * e)) : 0u;
            }
            BA[sg][r] = v;
          }
        uint2 A01[5], A23[5];
#pragma unroll
        for (int s = 0; s < 5; s++) {
          A01[s] = lds64(fb + f * 896 - 32 * (8 + 2 * s));
          A23[s] = lds64(fb + f * 896 - 32 * (7 + 2 * s));
        }
#pragma unroll
        for (int beta = 3; beta >= -1; beta--) {
          float z0[4] = {0.f, 0.f, 0.f, 0.f}, z1[4] = {0.f, 0.f, 0.f, 0.f};
#pragma unroll
          for (int sg = 0; sg < 3; sg++) {
            uint32_t u0, u1, u2, u3;
            ldsm_x4(ur[sg] + beta * 576, u0, u1, u2, u3);
            mma_bf16(z0, BA[sg][0], BA[sg][1], BA[sg][2], BA[sg][3], u0, u1);
            mma_bf16(z1, BA[sg][0], BA[sg][1], BA[sg][2], BA[sg][3], u2, u3);
          }
          const uint32_t b0 = pack_bf16(z0[0], z0[1]), b1 = pack_bf16(z1[0], z1[1]);
          const uint32_t b2 = pack_bf16(z0[2], z0[3]), b3 = pack_bf16(z1[2], z1[3]);
#pragma unroll
          for (int s = 0; s < 5; s++) {
            const int T = beta + 4 + s;
            if (T <= 7) {
              mma_bf16(ac[T - 3][0], A01[s].x, A01[s].y, A23[s].x, A23[s].y, b0, b1);
              mma_bf16(ac[T - 3][1], A01[s].x, A01[s].y, A23[s].x, A23[s].y, b2, b3);
            }
          }
        }
      }
      {
        const uint32_t nk = (uint32_t)__bfloat16_as_ushort(__float2bfloat16_rn(-k1024));
        uint32_t PC[5];
#pragma unroll
        for (int m = 0; m < 5; m++) {
          const int j = 8 * (125 + m) + g - 2 * t;
          PC[m] = ((j == 1020 || j == 1021) ? nk : 0u) | ((j == 1021 || j == 1022) ? (nk << 16) : 0u);
        }
#pragma unroll
        for (int k = 0; k < 2; k++) {
          const uint32_t ab = sbase + SB_U + rowaddr(UZ + 48 - 63 - k + krow) + (lane >> 4) * 16;
#pragma unroll
          for (int T = 3; T <= 7; T++) {
            uint32_t a0, a1, a2, a3;
            ldsm_x4(ab + (T - 3) * 576, a0, a1, a2, a3);
            mma_bf16(ac[T - 3][0], a0, a1, a2, a3, PC[1 + 2 * k], PC[2 * k]);
            mma_bf16(ac[T - 3][1], a0, a1, a2, a3, PC[2 + 2 * k], PC[1 + 2 * k]);
          }
        }
      }
      unsigned char* yb = sm + SB_Y + 16384;
#pragma unroll
      for (int T = 0; T <= 7; T++)
#pragma unroll
        for (int nu = 0; nu < 2; nu++)
#pragma unroll
          for (int hr = 0; hr < 2; hr++)
            *reinterpret_cast<float2*>(yb + ((yl ^ ((8 * (nu ^ hr)) * 4)) + (16 * T + 8 * hr) * 64)) =
                T >= 3 ? make_float2(ac[T >= 3 ? T - 3 : 0][nu][2 * hr], ac[T >= 3 ? T - 3 : 0][nu][2 * hr + 1]) : make_float2(0.f, 0.f);
    }
  }
  if (w < 2) asm volatile("bar.arrive %0, 96;" ::"r"(5 + bar) : "memory");
  TP(1, 7);
  named_bar(bar, 128);
  TP(1, 8);
  {
    const __nv_bfloat162 ds = *reinterpret_cast<const __nv_bfloat162*>(&dsk2);
    const int r0 = tid >> 2, ch = tid & 3;
    const int yo = (16 * (r0 ^ ((r0 >> 2) & 1)) + ((4 * ch) ^ (8 * (((r0 >> 1) ^ (r0 >> 3)) & 1)))) * 4;
    const int uo = SB_U + rowaddr(r0 + UZ) + ch * 8;
#pragma unroll
    for (int k = 0; k < 4; k++) {
      const float4 a = *reinterpret_cast<const float4*>(sm + SB_Y + yo + k * 2048);
      const float4 b = *reinterpret_cast<const float4*>(sm + SB_Y + 8192 + yo + k * 2048);
      const float4 c = *reinterpret_cast<const float4*>(sm + SB_Y + 16384 + yo + k * 2048);
      const uint2 uw = *reinterpret_cast<const uint2*>(sm + uo + k * 1152);
      const uint2 xw = *reinterpret_cast<const uint2*>(sm + SB_X + tid * 8 + k * 1024);
      const uint32_t y0 = pack_bf16(b.x + (a.x + c.x), b.y + (a.y + c.y)), y1 = pack_bf16(b.z + (a.z + c.z), b.w + (a.w + c.w));
      const __nv_bfloat162 h0 = __hadd2_rn(*reinterpret_cast<const __nv_bfloat162*>(&xw.x),
          __hadd2_rn(*reinterpret_cast<const __nv_bfloat162*>(&y0), __hmul2_rn(*reinterpret_cast<const __nv_bfloat162*>(&uw.x), ds)));
      const __nv_bfloat162 h1 = __hadd2_rn(*reinterpret_cast<const __nv_bfloat162*>(&xw.y),
          __hadd2_rn(*reinterpret_cast<const __nv_bfloat162*>(&y1), __hmul2_rn(*reinterpret_cast<const __nv_bfloat162*>(&uw.y), ds)));
      *reinterpret_cast<uint2*>(g_hT + (size_t)d * SEQ + tid * 4 + k * 512) =
          make_uint2(*reinterpret_cast<const uint32_t*>(&h0), *reinterpret_cast<const uint32_t*>(&h1));
    }
  }
  TS_MIN(8); TS_MAX(9);
  TP(1, 10);
#undef TPW
}

constexpr int G1_A     = 0;
constexpr int G1_W     = 7 * 16384;
constexpr int G1_STG   = G1_W + 3 * 32768;
constexpr int G1_STAT  = G1_STG + 16384;
constexpr int G1_CS    = G1_STAT + 1024;
constexpr int G1_BAR   = G1_CS + 1792;
constexpr int G1_TOTAL = G1_BAR + 128;

__device__ __forceinline__ float sigmoid_fast(float x) {
  float th; asm("tanh.approx.f32 %0, %1;" : "=f"(th) : "f"(0.5f * x));
  return fmaf(0.5f, th, 0.5f);
}

template <int NCB>
__device__ __forceinline__ void g1_pack(const float (&acc)[NCB * 8], uint32_t (&pk)[NCB * 4], const float* cs_g, const float* cs_u,
                                        float mb0, float rs0, float mb1, float rs1, int lane) {
  const int t = lane & 3;
  const float c0 = -mb0 * rs0, c1 = -mb1 * rs1;
#pragma unroll
  for (int cb = 0; cb < 2 * NCB; cb++) {
    const float2 sc = *reinterpret_cast<const float2*>((cb < NCB ? cs_g + cb * 8 : cs_u + (cb - NCB) * 8) + 2 * t);
    pk[2 * cb]     = pack_bf16(fmaf(acc[4 * cb + 0], rs0, c0 * sc.x), fmaf(acc[4 * cb + 1], rs0, c0 * sc.y));
    pk[2 * cb + 1] = pack_bf16(fmaf(acc[4 * cb + 2], rs1, c1 * sc.x), fmaf(acc[4 * cb + 3], rs1, c1 * sc.y));
  }
}
template <int NCB, int GRP>
__device__ __forceinline__ void g1_epi_group(const uint32_t (&pa)[NCB * 4], uint32_t buf,
                                             const CUtensorMap* tmHs, int fcol0, int row0, int lane) {
  uint32_t pk[4][2];
#pragma unroll
  for (int c = 0; c < 4; c++) {
#pragma unroll
    for (int h = 0; h < 2; h++) {
      const uint32_t gw = pa[2 * (GRP * 4 + c) + h], uw = pa[2 * (GRP * 4 + c + NCB) + h];
      pk[c][h] = pack_bf16(sigmoid_fast(bflo(gw)) * bflo(uw), sigmoid_fast(bfhi(gw)) * bfhi(uw));
    }
  }
  if (lane == 0) bulk_wait_read<1>();
  __syncwarp();
  const int r = (lane & 7) + 8 * ((lane >> 3) & 1);
#pragma unroll
  for (int h = 0; h < 2; h++) {
    const int chunk = 2 * h + (lane >> 4);
    stsm_x4(buf + r * 64 + ((chunk ^ ((r >> 1) & 3)) << 4), pk[2 * h][0], pk[2 * h][1], pk[2 * h + 1][0], pk[2 * h + 1][1]);
  }
  fence_async();
  __syncwarp();
  if (lane == 0) { tma2d_store(tmHs, buf, fcol0 + GRP * 32, row0); bulk_commit(); }
}

__global__ void __cluster_dims__(2, 1, 1) __launch_bounds__(384, 1)
k_g1(const __grid_constant__ CUtensorMap tmA, const __grid_constant__ CUtensorMap tmGa, const __grid_constant__ CUtensorMap tmGb,
     const __grid_constant__ CUtensorMap tmUa, const __grid_constant__ CUtensorMap tmUb, const __grid_constant__ CUtensorMap tmHs) {
  extern __shared__ __align__(1024) unsigned char smem[];
  const uint32_t sb = smem_u32(smem);
  const int tid = threadIdx.x, lane = tid & 31, warp = tid >> 5;
  const uint32_t rank = blockIdx.x & 1;
  const int pr = blockIdx.x >> 1;
  const int mt = 2 * (pr & 7) + rank;
  const int fj = pr >> 3;
  const uint32_t barA = sb + G1_BAR, barF = barA + 56, barE = barF + 24, barS = barE + 24;
  if (tid == 0) {
    if (sb & 1023) __trap();
    for (int i = 0; i < 7; i++) mbar_init(barA + 8 * i, 1);
    for (int i = 0; i < 3; i++) { mbar_init(barF + 8 * i, 1); mbar_init(barE + 8 * i, 4); }
    mbar_init(barS, 1);
    asm volatile("fence.mbarrier_init.release.cluster;" ::: "memory");
  }
  __syncthreads();
  cluster_arrive(); cluster_wait();
  pdl_launch();
  TS_MIN(10); TS_MAX(11);

  if (warp >= 8) {
    asm volatile("setmaxnreg.dec.sync.aligned.u32 24;");
    if (warp == 8) {
      if (lane == 0) {
        const CUtensorMap* tma = rank ? &tmUa : &tmGa;
        const CUtensorMap* tmb = rank ? &tmUb : &tmGb;
        for (int it = 0; it < 14; it++) {
          const int s = it % 3, rnd = it / 3;
          const bool pb = it >= 7;
          const int kb = pb ? it - 7 : it;
          if (it == 3) {
            pdl_wait();
            TS_MINT(12); TS_MAXT(13);
            for (int k = 0; k < 7; k++) {
              mbar_expect(barA + 8 * k, 16384);
              tma3d(sb + G1_A + k * 16384, &tmA, barA + 8 * k, 0, 64 * k, 2 * mt);
            }
          }
          if (rnd > 0) mbar_wait(barE + 8 * s, (rnd - 1) & 1);
          mbar_expect(barF + 8 * s, pb ? 24576 : 32768);
          const uint32_t dst = sb + G1_W + s * 32768 + rank * (pb ? 12288 : 16384);
          tma3d_mc(dst, pb ? tmb : tma, barF + 8 * s, 0, 64 * kb, 7 * fj + (pb ? 4 : 0), (uint16_t)3);
        }
      }
    } else if (warp == 11) {
      pdl_wait();
      float* cs = reinterpret_cast<float*>(smem + G1_CS);
      for (int i = lane; i < 448; i += 32) cs[i] = g_cs[(i >= 224 ? FF + i - 224 : i) + fj * 224];
      __syncwarp();
      if (lane == 0) mbar_arrive(barS);
    }
    __syncwarp();
    cluster_arrive(); cluster_wait();
  } else {
    asm volatile("setmaxnreg.inc.sync.aligned.u32 240;");
    const int wg = warp >> 2;
    const uint32_t remE = mapa(barE, rank ^ 1);
    const bool elect = (tid & 127) == 0;
    const int rloc = 64 * wg + 16 * (warp & 3);
    const uint32_t stg = sb + G1_STG + warp * 2048;
    float mb0, rs0, mb1, rs1;
    const float* cs = reinterpret_cast<const float*>(smem + G1_CS);
    uint32_t pkA[64];
    {
      float accA[128];
      float sh[8], sum[8], sq[8];
#pragma unroll
      for (int i = 0; i < 8; i++) { sum[i] = 0.f; sq[i] = 0.f; }
      const int ch = 2 * (warp & 3) + (lane >> 4), dd = lane & 15;
      const unsigned char* sbase = smem + G1_A + wg * 8192;
#pragma unroll 1
      for (int kb = 0; kb < 7; kb++) {
        const int s = kb % 3;
        mbar_wait(barA + 8 * kb, 0);
        mbar_wait(barF + 8 * s, (kb / 3) & 1);
#define TPW 0
        TP(2, kb);
        const uint64_t da = mk_desc(sb + G1_A + kb * 16384 + wg * 8192, 0, 1024, 1);
        const uint64_t db = mk_desc(sb + G1_W + s * 32768, 4096, 512, 2);
        wg_fence();
#pragma unroll
        for (int k = 0; k < 4; k++) wgmma_n256_t11(accA, da + k * 128, db + k * 64, (kb | k) != 0);
        wg_commit();
        if (kb > 0) {
          wg_wait<1>();
          if (elect) { const int sp = (kb - 1) % 3; mbar_arrive(barE + 8 * sp); mbar_arrive_cluster(remE + 8 * sp); }
        }
        if (kb == 0) {
          const uint4 v = *reinterpret_cast<const uint4*>(sbase + (ch << 4));
          sh[0] = bflo(v.x); sh[1] = bfhi(v.x); sh[2] = bflo(v.y); sh[3] = bfhi(v.y);
          sh[4] = bflo(v.z); sh[5] = bfhi(v.z); sh[6] = bflo(v.w); sh[7] = bfhi(v.w);
        }
#pragma unroll
        for (int it = 0; it < 4; it++) {
          const uint4 v = *reinterpret_cast<const uint4*>(sbase + kb * 16384 + (dd + 16 * it) * 128 + ((ch ^ (dd & 7)) << 4));
          const float f[8] = {bflo(v.x), bfhi(v.x), bflo(v.y), bfhi(v.y), bflo(v.z), bfhi(v.z), bflo(v.w), bfhi(v.w)};
#pragma unroll
          for (int i = 0; i < 8; i++) { const float a = f[i] - sh[i]; sum[i] += a; sq[i] = fmaf(a, a, sq[i]); }
        }
      }
      const bool b0 = lane & 1, b1 = lane & 2, b2 = lane & 4;
      float s4[4], q4[4], h4[4];
#pragma unroll
      for (int i = 0; i < 4; i++) {
        const float ss = b0 ? sum[i] : sum[i + 4], qs = b0 ? sq[i] : sq[i + 4];
        s4[i] = (b0 ? sum[i + 4] : sum[i]) + __shfl_xor_sync(0xffffffffu, ss, 1);
        q4[i] = (b0 ? sq[i + 4] : sq[i]) + __shfl_xor_sync(0xffffffffu, qs, 1);
        h4[i] = b0 ? sh[i + 4] : sh[i];
      }
      float s2[2], q2[2], h2[2];
#pragma unroll
      for (int i = 0; i < 2; i++) {
        const float ss = b1 ? s4[i] : s4[i + 2], qs = b1 ? q4[i] : q4[i + 2];
        s2[i] = (b1 ? s4[i + 2] : s4[i]) + __shfl_xor_sync(0xffffffffu, ss, 2);
        q2[i] = (b1 ? q4[i + 2] : q4[i]) + __shfl_xor_sync(0xffffffffu, qs, 2);
        h2[i] = b1 ? h4[i + 2] : h4[i];
      }
      float s1 = (b2 ? s2[1] : s2[0]) + __shfl_xor_sync(0xffffffffu, b2 ? s2[0] : s2[1], 4);
      float q1 = (b2 ? q2[1] : q2[0]) + __shfl_xor_sync(0xffffffffu, b2 ? q2[0] : q2[1], 4);
      const float h1 = b2 ? h2[1] : h2[0];
      s1 += __shfl_xor_sync(0xffffffffu, s1, 8);
      q1 += __shfl_xor_sync(0xffffffffu, q1, 8);
      const float ms = s1 * (1.0f / DM);
      const float var = fmaxf(q1 * (1.0f / DM) - ms * ms, 0.f);
      const float mb = bf16r(h1 + ms);
      const float den = bf16r(sqrtf(bf16r(bf16r(var) + 1e-5f)));
      const float rs = __fdiv_rn(1.0f, den);
      const int r0 = lane >> 2;
      const int src0 = ((r0 >> 2) & 1) | (r0 & 2) | ((r0 & 1) << 2);
      mb0 = __shfl_sync(0xffffffffu, mb, src0);      rs0 = __shfl_sync(0xffffffffu, rs, src0);
      mb1 = __shfl_sync(0xffffffffu, mb, src0 + 16); rs1 = __shfl_sync(0xffffffffu, rs, src0 + 16);
      wg_wait<0>();
      if (elect) { mbar_arrive(barE + 0); mbar_arrive_cluster(remE + 0); }
      TS_MIN(14); TS_MAX(15);
      TP(2, 7);
      mbar_wait(barS, 0);
      g1_pack<16>(accA, pkA, cs, cs + 224, mb0, rs0, mb1, rs1, lane);
      TS_MIN(16); TS_MAX(17);
    }
    const int row0 = mt * 128 + rloc;
    {
      float accB[96];
#define G1_PASSB(kb, EPI)                                                                                    \
      {                                                                                                      \
        constexpr int it = kb + 7, s = it % 3;                                                               \
        mbar_wait(barF + 8 * s, (it / 3) & 1);                                                               \
        TP(2, 8 + kb);                                                                                       \
        const uint64_t da = mk_desc(sb + G1_A + kb * 16384 + wg * 8192, 0, 1024, 1);                         \
        const uint64_t db = mk_desc(sb + G1_W + s * 32768, 4096, 512, 2);                                    \
        wg_fence();                                                                                          \
        _Pragma("unroll") for (int k = 0; k < 4; k++) wgmma_n192_t11(accB, da + k * 128, db + k * 64, (kb | k) != 0); \
        wg_commit();                                                                                         \
        if (kb > 0 && kb <= 4) {                                                                             \
          wg_wait<1>();                                                                                      \
          if (elect) { constexpr int sp = (it - 1) % 3; mbar_arrive(barE + 8 * sp); mbar_arrive_cluster(remE + 8 * sp); } \
        }                                                                                                    \
        EPI;                                                                                                 \
      }
#define G1_EPIA(G) g1_epi_group<16, G>(pkA, stg + (G & 1) * 1024, &tmHs, fj * 224, row0, lane)
#define G1_EPIB(G) g1_epi_group<12, G>(pkB, stg + (G & 1) * 1024, &tmHs, fj * 224 + 128, row0, lane)
      G1_PASSB(0, G1_EPIA(0));
      G1_PASSB(1, G1_EPIA(1));
      G1_PASSB(2, G1_EPIA(2));
      G1_PASSB(3, G1_EPIA(3));
      G1_PASSB(4, );
      G1_PASSB(5, );
      G1_PASSB(6, );
      wg_wait<0>();
      TS_MIN(20); TS_MAX(21);
      TP(2, 15);
      uint32_t pkB[48];
      g1_pack<12>(accB, pkB, cs + 128, cs + 352, mb0, rs0, mb1, rs1, lane);
      G1_EPIB(0); G1_EPIB(1); G1_EPIB(2);
    }
    if (lane == 0) bulk_wait<0>();
    __syncwarp();
    cluster_arrive(); cluster_wait();
    TS_MIN(22); TS_MAX(23);
  }
}

constexpr int G2_NST   = 5;
constexpr int G2_XB    = G2_NST * 32768;
constexpr int G2_HT    = G2_XB + 28672;
constexpr int G2_BAR   = G2_HT + 28672;
constexpr int G2_TOTAL = G2_BAR + 128;

__global__ void __cluster_dims__(2, 1, 1) __launch_bounds__(384, 1)
k_g2(const __grid_constant__ CUtensorMap tmH, const __grid_constant__ CUtensorMap tmWd, const __grid_constant__ CUtensorMap tmR,
     const __grid_constant__ CUtensorMap tmO) {
  extern __shared__ __align__(1024) unsigned char smem[];
  const uint32_t sb = smem_u32(smem);
  const int tid = threadIdx.x, lane = tid & 31, warp = tid >> 5;
  const uint32_t rank = blockIdx.x & 1;
  const int pr = blockIdx.x >> 1;
  const int nq = pr & 3, mt = pr >> 2;
  const uint32_t barF = sb + G2_BAR, barE = barF + 8 * G2_NST, barR = barE + 8 * G2_NST;
  if (tid == 0) {
    if (sb & 1023) __trap();
    for (int i = 0; i < G2_NST; i++) { mbar_init(barF + 8 * i, 1); mbar_init(barE + 8 * i, 2); }
    mbar_init(barR, 1);
    asm volatile("fence.mbarrier_init.release.cluster;" ::: "memory");
  }
  __syncthreads();
  cluster_arrive();
  TS_MIN(24); TS_MAX(25);

  if (warp >= 8) {
    if (warp == 8 && lane == 0) {
      const int k0 = rank * 896;
      for (int s = 0; s < G2_NST; s++) {
        mbar_expect(barF + 8 * s, 32768);
        tma2d(sb + s * 32768 + 16384, &tmWd, barF + 8 * s, 112 * nq, k0 + 64 * s);
        tma2d(sb + s * 32768 + 24576, &tmWd, barF + 8 * s, 112 * nq + 64, k0 + 64 * s);
      }
      pdl_wait();
      if (blockIdx.x == 0) g_cnt[0] = 0u;
      TS_MINT(26); TS_MAXT(27);
      for (int s = 0; s < G2_NST; s++) tma2d(sb + s * 32768, &tmH, barF + 8 * s, k0 + 64 * s, 128 * mt);
      mbar_expect(barR, 28672);
      tma3d(sb + G2_HT, &tmR, barR, 0, 112 * nq, 2 * mt);
      for (int it = G2_NST; it < 14; it++) {
        const int s = it % G2_NST, rnd = it / G2_NST;
        mbar_wait(barE + 8 * s, (rnd - 1) & 1);
        mbar_expect(barF + 8 * s, 32768);
        tma2d(sb + s * 32768, &tmH, barF + 8 * s, k0 + 64 * it, 128 * mt);
        tma2d(sb + s * 32768 + 16384, &tmWd, barF + 8 * s, 112 * nq, k0 + 64 * it);
        tma2d(sb + s * 32768 + 24576, &tmWd, barF + 8 * s, 112 * nq + 64, k0 + 64 * it);
      }
    }
    __syncwarp();
    cluster_wait();
    cluster_arrive(); cluster_wait();
  } else {
    const int wg = warp >> 2, wq = warp & 3;
    const bool elect = (tid & 127) == 0;
    float acc[56];
#pragma unroll 1
    for (int it = 0; it < 14; it++) {
      const int s = it % G2_NST;
      mbar_wait(barF + 8 * s, (it / G2_NST) & 1);
      TP(3, it);
      const uint64_t da = mk_desc(sb + s * 32768 + wg * 8192, 0, 1024, 1);
      const uint64_t db = mk_desc(sb + s * 32768 + 16384, 8192, 1024, 1);
      wg_fence();
#pragma unroll
      for (int k = 0; k < 4; k++) wgmma_n112_t01(acc, da + k * 2, db + k * 128, (it | k) != 0);
      wg_commit();
      if (it > 0) {
        wg_wait<1>();
        if (elect) mbar_arrive(barE + 8 * ((it - 1) % G2_NST));
      }
    }
    wg_wait<0>();
    TS_MIN(28); TS_MAX(29);
    TP(3, 14);
    cluster_wait();
    {
      const uint32_t rx = mapa(sb + G2_XB, rank ^ 1) + tid * 16;
#pragma unroll
      for (int c = 0; c < 7; c++) {
        const float v0 = rank ? acc[4 * c + 0] : acc[28 + 4 * c + 0], v1 = rank ? acc[4 * c + 1] : acc[28 + 4 * c + 1];
        const float v2 = rank ? acc[4 * c + 2] : acc[28 + 4 * c + 2], v3 = rank ? acc[4 * c + 3] : acc[28 + 4 * c + 3];
        asm volatile("st.shared::cluster.v4.f32 [%0], {%1,%2,%3,%4};" ::"r"(rx + c * 4096), "f"(v0), "f"(v1), "f"(v2), "f"(v3) : "memory");
      }
    }
    cluster_arrive(); cluster_wait();
    mbar_wait(barR, 0);
    TP(3, 15);
    uint32_t pk[7][2];
    const uint32_t htb = sb + G2_HT + wg * 14336;
#pragma unroll
    for (int c = 0; c < 7; c++) {
      const float4 o = *reinterpret_cast<const float4*>(smem + G2_XB + c * 4096 + tid * 16);
      const float m0 = (rank ? acc[28 + 4 * c + 0] : acc[4 * c + 0]) + o.x, m1 = (rank ? acc[28 + 4 * c + 1] : acc[4 * c + 1]) + o.y;
      const float m2 = (rank ? acc[28 + 4 * c + 2] : acc[4 * c + 2]) + o.z, m3 = (rank ? acc[28 + 4 * c + 3] : acc[4 * c + 3]) + o.w;
      uint32_t h0, h1;
      const int dd = 8 * (7 * rank + c) + (lane & 7);
      const int tc = 2 * wq + ((lane >> 3) & 1);
      ldsm_x2_t(htb + dd * 128 + ((tc ^ (dd & 7)) << 4), h0, h1);
      pk[c][0] = pack_bf16(bflo(h0) + bf16r(m0), bfhi(h0) + bf16r(m1));
      pk[c][1] = pack_bf16(bflo(h1) + bf16r(m2), bfhi(h1) + bf16r(m3));
    }
    const uint32_t stg = sb + warp * 1792;
    const int r = (lane & 7) + 8 * ((lane >> 3) & 1);
#pragma unroll
    for (int c = 0; c < 6; c += 2)
      stsm_x4(stg + r * 112 + (c + (lane >> 4)) * 16, pk[c][0], pk[c][1], pk[c + 1][0], pk[c + 1][1]);
    stsm_x2(stg + r * 112 + 6 * 16, pk[6][0], pk[6][1]);
    fence_async();
    __syncwarp();
    if (lane == 0) {
      tma2d_store(&tmO, stg, 112 * nq + 56 * rank, 128 * mt + 64 * wg + 16 * wq);
      bulk_commit();
      bulk_wait<0>();
    }
    TS_MIN(30); TS_MAX(31);
  }
}

typedef CUresult (*EncFn)(CUtensorMap*, CUtensorMapDataType, cuuint32_t, void*, const cuuint64_t*, const cuuint64_t*,
                          const cuuint32_t*, const cuuint32_t*, CUtensorMapInterleave, CUtensorMapSwizzle,
                          CUtensorMapL2promotion, CUtensorMapFloatOOBfill);

static void make_map(EncFn enc, CUtensorMap* tm, const void* ptr, int rank, const uint64_t* dims, const uint64_t* strides_bytes,
                     const uint32_t* box, CUtensorMapSwizzle swz) {
  cuuint64_t gd[3], gs[2]; cuuint32_t bd[3], es[3] = {1, 1, 1};
  for (int i = 0; i < rank; i++) { gd[i] = dims[i]; bd[i] = box[i]; }
  for (int i = 0; i < rank - 1; i++) gs[i] = strides_bytes[i];
  enc(tm, CU_TENSOR_MAP_DATA_TYPE_BFLOAT16, rank, const_cast<void*>(ptr), gd, gs, bd, es, CU_TENSOR_MAP_INTERLEAVE_NONE, swz,
      CU_TENSOR_MAP_L2_PROMOTION_L2_128B, CU_TENSOR_MAP_FLOAT_OOB_FILL_NONE);
}

template <class K, class... Args>
static void launch_k(K kern, int grid, int block, int smem, bool pdl, Args... args) {
  cudaLaunchConfig_t cfg = {};
  cfg.gridDim = dim3(grid); cfg.blockDim = dim3(block); cfg.dynamicSmemBytes = smem; cfg.stream = cudaStreamPerThread;
  cudaLaunchAttribute at[1];
  at[0].id = cudaLaunchAttributeProgrammaticStreamSerialization;
  at[0].val.programmaticStreamSerializationAllowed = 1;
  cfg.attrs = at; cfg.numAttrs = pdl ? 1 : 0;
  cudaLaunchKernelEx(&cfg, kern, args...);
}

extern "C" void kernel_launch(void* const* d_in, const int* in_sizes, int n_in, void* d_out, int out_size) {
  const bf16* x   = (const bf16*)d_in[0];
  const bf16* Are = (const bf16*)d_in[1];
  const bf16* Aim = (const bf16*)d_in[2];
  const bf16* Bre = (const bf16*)d_in[3];
  const bf16* Bim = (const bf16*)d_in[4];
  const bf16* Cre = (const bf16*)d_in[5];
  const bf16* Cim = (const bf16*)d_in[6];
  const bf16* ldt = (const bf16*)d_in[7];
  const bf16* dsk = (const bf16*)d_in[8];
  const bf16* wg  = (const bf16*)d_in[10];
  const bf16* wu  = (const bf16*)d_in[11];
  const bf16* wd  = (const bf16*)d_in[12];

  static EncFn enc = nullptr;
  static void *p_hT = nullptr, *p_H = nullptr;
  if (!enc) {
    void* fn = nullptr; cudaDriverEntryPointQueryResult qr;
    cudaGetDriverEntryPoint("cuTensorMapEncodeTiled", &fn, cudaEnableDefault, &qr);
    enc = (EncFn)fn;
    cudaGetSymbolAddress(&p_hT, g_hT);
    cudaGetSymbolAddress(&p_H, g_H);
    cudaFuncSetAttribute(k_ssm, cudaFuncAttributeMaxDynamicSharedMemorySize, FRONT_SMEM);
    cudaFuncSetAttribute(k_g1, cudaFuncAttributeMaxDynamicSharedMemorySize, G1_TOTAL);
    cudaFuncSetAttribute(k_g2, cudaFuncAttributeMaxDynamicSharedMemorySize, G2_TOTAL);
  }
  CUtensorMap tmA, tmGa, tmGb, tmUa, tmUb, tmHs, tmH, tmWd, tmR, tmO;
  {
    uint64_t dims[3] = {64, DM, SEQ / 64}, st[2] = {SEQ * 2, 128};
    uint32_t box[3] = {64, 64, 2}, boxr[3] = {64, 112, 2};
    make_map(enc, &tmA, p_hT, 3, dims, st, box, CU_TENSOR_MAP_SWIZZLE_128B);
    make_map(enc, &tmR, p_hT, 3, dims, st, boxr, CU_TENSOR_MAP_SWIZZLE_128B);
  }
  {
    uint64_t dims[3] = {32, DM, FF / 32}, st[2] = {FF * 2, 64};
    uint32_t boxa[3] = {32, 64, 4}, boxb[3] = {32, 64, 3};
    make_map(enc, &tmGa, wg, 3, dims, st, boxa, CU_TENSOR_MAP_SWIZZLE_64B);
    make_map(enc, &tmGb, wg, 3, dims, st, boxb, CU_TENSOR_MAP_SWIZZLE_64B);
    make_map(enc, &tmUa, wu, 3, dims, st, boxa, CU_TENSOR_MAP_SWIZZLE_64B);
    make_map(enc, &tmUb, wu, 3, dims, st, boxb, CU_TENSOR_MAP_SWIZZLE_64B);
  }
  {
    uint64_t dims[2] = {FF, SEQ}, st[1] = {FF * 2};
    uint32_t boxs[2] = {32, 16}, boxl[2] = {64, 128};
    make_map(enc, &tmHs, p_H, 2, dims, st, boxs, CU_TENSOR_MAP_SWIZZLE_64B);
    make_map(enc, &tmH, p_H, 2, dims, st, boxl, CU_TENSOR_MAP_SWIZZLE_128B);
  }
  {
    uint64_t dims[2] = {DM, FF}, st[1] = {DM * 2};
    uint32_t box[2] = {64, 64};
    make_map(enc, &tmWd, wd, 2, dims, st, box, CU_TENSOR_MAP_SWIZZLE_128B);
  }
  {
    uint64_t dims[2] = {DM, SEQ}, st[1] = {DM * 2};
    uint32_t box[2] = {56, 16};
    make_map(enc, &tmO, d_out, 2, dims, st, box, CU_TENSOR_MAP_SWIZZLE_NONE);
  }
  launch_k(k_ssm, 132, 512, FRONT_SMEM, false, Are, Aim, Bre, Bim, Cre, Cim, ldt, dsk, x, wg, wu, wd);
  launch_k(k_g1, 128, 384, G1_TOTAL, true, tmA, tmGa, tmGb, tmUa, tmUb, tmHs);
  launch_k(k_g2, 128, 384, G2_TOTAL, true, tmH, tmWd, tmR, tmO);
}
```

```cpp
#include <cuda_runtime.h>
#include <cuda_bf16.h>
#include <cuda_fp16.h>
#include <cuda.h>
#include <stdint.h>

typedef __nv_bfloat16 bf16;

constexpr int SEQ = 2048;
constexpr int DM  = 448;
constexpr int NM  = 256;
constexpr int FF  = 1792;

__device__ __align__(1024) bf16  g_uT[DM * SEQ];
__device__ __align__(1024) bf16  g_xT[DM * SEQ];
__device__ __align__(1024) bf16  g_hT[DM * SEQ];
__device__ __align__(1024) bf16  g_P[SEQ * FF];
__device__ __align__(1024) float g_cs[2 * FF];
#define TQ(i)
#define TS_MIN(i)
#define TS_MAX(i)
#define TS_MINT(i)
#define TP(k, i)
#define TP_INIT(k)
#define TP_DUMP(k)
#define TS_MAXT(i)

__device__ __forceinline__ uint32_t smem_u32(const void* p) { return (uint32_t)__cvta_generic_to_shared(p); }
__device__ __forceinline__ float bf16r(float v) { return __bfloat162float(__float2bfloat16_rn(v)); }
__device__ __forceinline__ float bflo(uint32_t w) { return __uint_as_float(w << 16); }
__device__ __forceinline__ float bfhi(uint32_t w) { return __uint_as_float(w & 0xffff0000u); }
__device__ __forceinline__ uint32_t pack_bf16(float lo, float hi) {
  uint32_t r; asm("cvt.rn.bf16x2.f32 %0, %1, %2;" : "=r"(r) : "f"(hi), "f"(lo)); return r;
}
__device__ __forceinline__ uint32_t pack_f16(float lo, float hi) {
  uint32_t r; asm("cvt.rn.f16x2.f32 %0, %1, %2;" : "=r"(r) : "f"(hi), "f"(lo)); return r;
}
__device__ __forceinline__ float ex2f(float x) { float r; asm("ex2.approx.ftz.f32 %0, %1;" : "=f"(r) : "f"(x)); return r; }
__device__ __forceinline__ void pdl_launch() { asm volatile("griddepcontrol.launch_dependents;"); }
__device__ __forceinline__ void pdl_wait() { asm volatile("griddepcontrol.wait;" ::: "memory"); }

__device__ __forceinline__ void mbar_init(uint32_t a, int c) { asm volatile("mbarrier.init.shared::cta.b64 [%0], %1;" ::"r"(a), "r"(c)); }
__device__ __forceinline__ void mbar_expect(uint32_t a, uint32_t bytes) {
  asm volatile("mbarrier.arrive.expect_tx.shared::cta.b64 _, [%0], %1;" ::"r"(a), "r"(bytes) : "memory");
}
__device__ __forceinline__ void mbar_arrive(uint32_t a) { asm volatile("mbarrier.arrive.shared::cta.b64 _, [%0];" ::"r"(a) : "memory"); }
__device__ __forceinline__ void mbar_arrive_cluster(uint32_t remote_a) {
  asm volatile("mbarrier.arrive.shared::cluster.b64 _, [%0];" ::"r"(remote_a) : "memory");
}
__device__ __forceinline__ void mbar_wait(uint32_t a, uint32_t ph) {
  uint32_t ok; int it = 0;
  do {
    asm volatile("{.reg .pred p; mbarrier.try_wait.parity.shared::cta.b64 p, [%1], %2; selp.u32 %0,1,0,p;}"
                 : "=r"(ok) : "r"(a), "r"(ph) : "memory");
  } while (!ok && ++it < (1 << 24));
}
__device__ __forceinline__ void flag_wait(const unsigned int* p, unsigned int target) {
  unsigned int v; int it = 0;
  asm volatile("ld.acquire.gpu.global.u32 %0, [%1];" : "=r"(v) : "l"(p) : "memory");
  if ((int)(v - target) >= 0) return;
  while (true) {
    __nanosleep(32);
    asm volatile("ld.relaxed.gpu.global.u32 %0, [%1];" : "=r"(v) : "l"(p) : "memory");
    if ((int)(v - target) >= 0 || ++it > (1 << 22)) break;
  }
  asm volatile("ld.acquire.gpu.global.u32 %0, [%1];" : "=r"(v) : "l"(p) : "memory");
}
__device__ __forceinline__ uint4 ld_relaxed_v4(const uint4* p) {
  uint4 v; asm volatile("ld.relaxed.gpu.global.v4.u32 {%0,%1,%2,%3}, [%4];" : "=r"(v.x), "=r"(v.y), "=r"(v.z), "=r"(v.w) : "l"(p) : "memory"); return v;
}
__device__ __forceinline__ void st_relaxed_v4(uint4* p, uint32_t a, uint32_t b, uint32_t c, uint32_t d) {
  asm volatile("st.relaxed.gpu.global.v4.u32 [%0], {%1,%2,%3,%4};" ::"l"(p), "r"(a), "r"(b), "r"(c), "r"(d) : "memory");
}
__device__ __forceinline__ uint32_t mapa(uint32_t a, uint32_t rank) {
  uint32_t r; asm volatile("mapa.shared::cluster.u32 %0, %1, %2;" : "=r"(r) : "r"(a), "r"(rank)); return r;
}
__device__ __forceinline__ void cluster_arrive() { asm volatile("barrier.cluster.arrive.release.aligned;" ::: "memory"); }
__device__ __forceinline__ void cluster_wait() { asm volatile("barrier.cluster.wait.acquire.aligned;" ::: "memory"); }
__device__ __forceinline__ void fence_async() { asm volatile("fence.proxy.async.shared::cta;" ::: "memory"); }
__device__ __forceinline__ void named_bar(int id, int n) { asm volatile("bar.sync %0, %1;" ::"r"(id), "r"(n) : "memory"); }

__device__ __forceinline__ void tma2d(uint32_t dst, const CUtensorMap* tm, uint32_t bar, int c0, int c1) {
  asm volatile("cp.async.bulk.tensor.2d.shared::cluster.global.mbarrier::complete_tx::bytes [%0], [%1, {%3,%4}], [%2];"
               ::"r"(dst), "l"(tm), "r"(bar), "r"(c0), "r"(c1) : "memory");
}
__device__ __forceinline__ void tma3d(uint32_t dst, const CUtensorMap* tm, uint32_t bar, int c0, int c1, int c2) {
  asm volatile("cp.async.bulk.tensor.3d.shared::cluster.global.mbarrier::complete_tx::bytes [%0], [%1, {%3,%4,%5}], [%2];"
               ::"r"(dst), "l"(tm), "r"(bar), "r"(c0), "r"(c1), "r"(c2) : "memory");
}
__device__ __forceinline__ void tma3d_mc(uint32_t dst, const CUtensorMap* tm, uint32_t bar, int c0, int c1, int c2, uint16_t mask) {
  asm volatile("cp.async.bulk.tensor.3d.shared::cluster.global.mbarrier::complete_tx::bytes.multicast::cluster [%0], [%1, {%3,%4,%5}], [%2], %6;"
               ::"r"(dst), "l"(tm), "r"(bar), "r"(c0), "r"(c1), "r"(c2), "h"(mask) : "memory");
}
__device__ __forceinline__ void tma2d_store(const CUtensorMap* tm, uint32_t src, int c0, int c1) {
  asm volatile("cp.async.bulk.tensor.2d.global.shared::cta.bulk_group [%0, {%2,%3}], [%1];"
               ::"l"(tm), "r"(src), "r"(c0), "r"(c1) : "memory");
}
__device__ __forceinline__ void bulk_commit() { asm volatile("cp.async.bulk.commit_group;" ::: "memory"); }
template <int N> __device__ __forceinline__ void bulk_wait_read() { asm volatile("cp.async.bulk.wait_group.read %0;" ::"n"(N) : "memory"); }
template <int N> __device__ __forceinline__ void bulk_wait() { asm volatile("cp.async.bulk.wait_group %0;" ::"n"(N) : "memory"); }
__device__ __forceinline__ void prefetch_tm(const CUtensorMap* tm) { asm volatile("prefetch.tensormap [%0];" ::"l"(tm) : "memory"); }

__device__ __forceinline__ void wg_fence() { asm volatile("wgmma.fence.sync.aligned;" ::: "memory"); }
__device__ __forceinline__ void wg_commit() { asm volatile("wgmma.commit_group.sync.aligned;" ::: "memory"); }
template <int N> __device__ __forceinline__ void wg_wait() { asm volatile("wgmma.wait_group.sync.aligned %0;" ::"n"(N) : "memory"); }
__device__ __forceinline__ uint64_t mk_desc(uint32_t addr, uint32_t lbo, uint32_t sbo, uint32_t swz) {
  return (uint64_t)((addr & 0x3FFFF) >> 4) | ((uint64_t)(lbo >> 4) << 16) | ((uint64_t)(sbo >> 4) << 32) | ((uint64_t)swz << 62);
}
__device__ __forceinline__ void ldsm_x4(uint32_t a, uint32_t& r0, uint32_t& r1, uint32_t& r2, uint32_t& r3) {
  asm volatile("ldmatrix.sync.aligned.m8n8.x4.shared.b16 {%0,%1,%2,%3}, [%4];" : "=r"(r0), "=r"(r1), "=r"(r2), "=r"(r3) : "r"(a));
}
__device__ __forceinline__ void ldsm_x4_t(uint32_t a, uint32_t& r0, uint32_t& r1, uint32_t& r2, uint32_t& r3) {
  asm volatile("ldmatrix.sync.aligned.m8n8.x4.trans.shared.b16 {%0,%1,%2,%3}, [%4];" : "=r"(r0), "=r"(r1), "=r"(r2), "=r"(r3) : "r"(a));
}
__device__ __forceinline__ void ldsm_x2_t(uint32_t a, uint32_t& r0, uint32_t& r1) {
  asm volatile("ldmatrix.sync.aligned.m8n8.x2.trans.shared.b16 {%0,%1}, [%2];" : "=r"(r0), "=r"(r1) : "r"(a));
}
__device__ __forceinline__ void stsm_x4(uint32_t a, uint32_t r0, uint32_t r1, uint32_t r2, uint32_t r3) {
  asm volatile("stmatrix.sync.aligned.m8n8.x4.shared.b16 [%0], {%1,%2,%3,%4};" ::"r"(a), "r"(r0), "r"(r1), "r"(r2), "r"(r3) : "memory");
}
__device__ __forceinline__ void stsm_x2(uint32_t a, uint32_t r0, uint32_t r1) {
  asm volatile("stmatrix.sync.aligned.m8n8.x2.shared.b16 [%0], {%1,%2};" ::"r"(a), "r"(r0), "r"(r1) : "memory");
}
__device__ __forceinline__ uint32_t lds32(uint32_t a) { uint32_t r; asm volatile("ld.shared.u32 %0, [%1];" : "=r"(r) : "r"(a)); return r; }
__device__ __forceinline__ void mma_bf16(float (&c)[4], uint32_t a0, uint32_t a1, uint32_t a2, uint32_t a3, uint32_t b0, uint32_t b1) {
  asm volatile("mma.sync.aligned.m16n8k16.row.col.f32.bf16.bf16.f32 {%0,%1,%2,%3}, {%4,%5,%6,%7}, {%8,%9}, {%0,%1,%2,%3};"
               : "+f"(c[0]), "+f"(c[1]), "+f"(c[2]), "+f"(c[3]) : "r"(a0), "r"(a1), "r"(a2), "r"(a3), "r"(b0), "r"(b1));
}
__device__ __forceinline__ void mma_f16(float (&c)[4], uint32_t a0, uint32_t a1, uint32_t a2, uint32_t a3, uint32_t b0, uint32_t b1) {
  asm volatile("mma.sync.aligned.m16n8k16.row.col.f32.f16.f16.f32 {%0,%1,%2,%3}, {%4,%5,%6,%7}, {%8,%9}, {%0,%1,%2,%3};"
               : "+f"(c[0]), "+f"(c[1]), "+f"(c[2]), "+f"(c[3]) : "r"(a0), "r"(a1), "r"(a2), "r"(a3), "r"(b0), "r"(b1));
}
__device__ __forceinline__ void cp_async16(uint32_t dst, const void* src) {
  asm volatile("cp.async.cg.shared.global [%0], [%1], 16;" ::"r"(dst), "l"(src) : "memory");
}
__device__ __forceinline__ void cp_async_wait_all() { asm volatile("cp.async.wait_all;" ::: "memory"); }

__device__ unsigned int g_epoch;
__device__ unsigned int g_cnt[16];
__device__ unsigned int g_cnt2[256];
__device__ unsigned int g_done;

constexpr int LN_PITCH = 912;
constexpr int LN_STAT  = 16 * LN_PITCH;
constexpr int LN_SMEM  = LN_STAT + 7 * 128;
__device__ __forceinline__ void ln1_load(const bf16* __restrict__ x, int tile, unsigned char* sm) {
  const int r = (threadIdx.x >> 4) & 15, c = threadIdx.x & 15;
  const uint32_t dst = smem_u32(sm) + r * LN_PITCH + c * 16;
  const bf16* src = x + (size_t)(tile * 16 + r) * DM + c * 8;
#pragma unroll
  for (int k = 0; k < 4; k++)
    if (k < 3 || c < 8) cp_async16(dst + k * 256, src + k * 128);
}
__device__ __forceinline__ void ln1_tile(int tile, unsigned char* sm) {
  const uint32_t sb = smem_u32(sm);
  const int lane = threadIdx.x & 31, w = (threadIdx.x >> 5) - 8;
  const int g = lane >> 2, t = lane & 3;
  cp_async_wait_all();
  named_bar(14, 256);
  if (w < 7) {
    float s1[4] = {0.f, 0.f, 0.f, 0.f}, qa[4] = {0.f, 0.f, 0.f, 0.f}, qb[4] = {0.f, 0.f, 0.f, 0.f};
    const uint32_t ad = sb + ((lane & 7) + 8 * ((lane >> 3) & 1)) * LN_PITCH + (lane >> 4) * 16 + w * 128;
#pragma unroll
    for (int k = 0; k < 4; k++) {
      uint32_t a0, a1, a2, a3;
      ldsm_x4(ad + k * 32, a0, a1, a2, a3);
      mma_bf16(s1, a0, a1, a2, a3, 0x3f803f80u, 0x3f803f80u);
      mma_bf16(qa, a0, a1, a2, a3, a0, a2);
      mma_bf16(qb, a0, a1, a2, a3, a1, a3);
    }
    if (t == (g >> 1)) {
      float2* st = reinterpret_cast<float2*>(sm + LN_STAT) + w * 16;
      st[g]     = make_float2(s1[0], (g & 1) ? qa[1] : qa[0]);
      st[g + 8] = make_float2(s1[2], (g & 1) ? qb[3] : qb[2]);
    }
  }
  named_bar(14, 256);
  if (w < 7) {
    float mb[4], rd[4];
    {
      const float2* st = reinterpret_cast<const float2*>(sm + LN_STAT) + (lane & 15);
      float sx = 0.f, sy = 0.f;
#pragma unroll
      for (int i = 0; i < 7; i++) { const float2 p = st[16 * i]; sx += p.x; sy += p.y; }
      const float mean = sx * (1.0f / DM);
      const float var = fmaxf(sy * (1.0f / DM) - mean * mean, 0.f);
      const float m = bf16r(mean);
      const float r = __fdiv_rn(1.0f, bf16r(sqrtf(bf16r(bf16r(var) + 1e-5f))));
#pragma unroll
      for (int e = 0; e < 4; e++) {
        mb[e] = __shfl_sync(0xffffffffu, m, 4 * t + e);
        rd[e] = __shfl_sync(0xffffffffu, r, 4 * t + e);
      }
    }
    const int r8 = lane & 7;
    const int tok = 4 * (r8 >> 1) + (r8 & 1) + 2 * ((lane >> 3) & 1);
    const uint32_t ad = sb + tok * LN_PITCH + (w * 64 + (lane >> 4) * 8) * 2;
    const size_t go = (size_t)(tile * DM + w * 64 + g) * 16 + 4 * t;
#pragma unroll
    for (int k = 0; k < 4; k++) {
      uint32_t v[4];
      ldsm_x4_t(ad + k * 32, v[0], v[1], v[2], v[3]);
#pragma unroll
      for (int h = 0; h < 2; h++) {
        const uint32_t d0 = pack_bf16(bflo(v[2 * h]) - mb[0], bfhi(v[2 * h]) - mb[1]);
        const uint32_t d1 = pack_bf16(bflo(v[2 * h + 1]) - mb[2], bfhi(v[2 * h + 1]) - mb[3]);
        const size_t o = go + (size_t)(16 * k + 8 * h) * 16;
        *reinterpret_cast<uint2*>(g_uT + o) = make_uint2(pack_bf16(bflo(d0) * rd[0], bfhi(d0) * rd[1]), pack_bf16(bflo(d1) * rd[2], bfhi(d1) * rd[3]));
        *reinterpret_cast<uint2*>(g_xT + o) = make_uint2(v[2 * h], v[2 * h + 1]);
      }
    }
    asm volatile("bar.arrive 12, 256;" ::: "memory");
  } else {
    named_bar(12, 256);
    if (lane == 0) {
      __threadfence();
      asm volatile("red.relaxed.gpu.global.add.u32 [%0], 1;" ::"l"(&g_cnt[7]) : "memory");
    }
    __syncwarp();
  }
}

constexpr int CS_SMEM = 448 * 64 + 16 * 128;
__device__ __forceinline__ void colsum_load(const bf16* __restrict__ wg, const bf16* __restrict__ wu, int b2, unsigned char* sm) {
  const bf16* W = (b2 >= 56 ? wu : wg) + (b2 % 56) * 32;
  const uint32_t sb = smem_u32(sm);
#pragma unroll
  for (int k = 0; k < 7; k++)
    cp_async16(sb + threadIdx.x * 16 + k * 4096, W + (size_t)(threadIdx.x >> 2) * FF + (threadIdx.x & 3) * 8 + (size_t)k * 64 * FF);
}
__device__ __forceinline__ void colsum_reduce(unsigned char* sm) {
  const int lane = threadIdx.x & 31, w = threadIdx.x >> 5;
  if (w >= 7) return;
  float acc[4][4];
#pragma unroll
  for (int i = 0; i < 4; i++) { acc[i][0] = acc[i][1] = acc[i][2] = acc[i][3] = 0.f; }
  const uint32_t ad = smem_u32(sm) + (w * 64 + (lane & 15)) * 64 + (lane >> 4) * 16;
#pragma unroll
  for (int k = 0; k < 4; k++) {
#pragma unroll
    for (int h = 0; h < 2; h++) {
      uint32_t b0, b1, b2, b3;
      ldsm_x4_t(ad + k * 1024 + h * 32, b0, b1, b2, b3);
      mma_bf16(acc[2 * h], 0x3f803f80u, 0x3f803f80u, 0x3f803f80u, 0x3f803f80u, b0, b1);
      mma_bf16(acc[2 * h + 1], 0x3f803f80u, 0x3f803f80u, 0x3f803f80u, 0x3f803f80u, b2, b3);
    }
  }
  if (lane < 4) {
    float* sf = reinterpret_cast<float*>(sm + 448 * 64) + w * 32 + 2 * lane;
#pragma unroll
    for (int i = 0; i < 4; i++) *reinterpret_cast<float2*>(sf + 8 * i) = make_float2(acc[i][0], acc[i][1]);
  }
}
__device__ __forceinline__ void colsum_store(int b2, unsigned char* sm) {
  const float* sf = reinterpret_cast<const float*>(sm + 448 * 64);
  const int lane = threadIdx.x & 31;
  float s = 0.f;
#pragma unroll
  for (int i = 0; i < 7; i++) s += sf[i * 32 + lane];
  g_cs[(b2 >= 56 ? FF : 0) + (b2 % 56) * 32 + lane] = s;
}
__device__ __forceinline__ void wgmma_rs_n96(float (&d)[48], uint32_t a0, uint32_t a1, uint32_t a2, uint32_t a3, uint64_t db, int sc) {
  asm volatile("{\n.reg .pred p;\nsetp.ne.b32 p, %53, 0;\n"
    "wgmma.mma_async.sync.aligned.m64n96k16.f32.bf16.bf16 {%0, %1, %2, %3, %4, %5, %6, %7, %8, %9, %10, %11, %12, %13, %14, %15, %16, %17, %18, %19, %20, %21, %22, %23, %24, %25, %26, %27, %28, %29, %30, %31, %32, %33, %34, %35, %36, %37, %38, %39, %40, %41, %42, %43, %44, %45, %46, %47}, {%48, %49, %50, %51}, %52, p, 1, 1, 1;\n}\n"
    : "+f"(d[0]), "+f"(d[1]), "+f"(d[2]), "+f"(d[3]), "+f"(d[4]), "+f"(d[5]), "+f"(d[6]), "+f"(d[7]), "+f"(d[8]), "+f"(d[9]), "+f"(d[10]), "+f"(d[11]), "+f"(d[12]), "+f"(d[13]), "+f"(d[14]), "+f"(d[15]), "+f"(d[16]), "+f"(d[17]), "+f"(d[18]), "+f"(d[19]), "+f"(d[20]), "+f"(d[21]), "+f"(d[22]), "+f"(d[23]), "+f"(d[24]), "+f"(d[25]), "+f"(d[26]), "+f"(d[27]), "+f"(d[28]), "+f"(d[29]), "+f"(d[30]), "+f"(d[31]), "+f"(d[32]), "+f"(d[33]), "+f"(d[34]), "+f"(d[35]), "+f"(d[36]), "+f"(d[37]), "+f"(d[38]), "+f"(d[39]), "+f"(d[40]), "+f"(d[41]), "+f"(d[42]), "+f"(d[43]), "+f"(d[44]), "+f"(d[45]), "+f"(d[46]), "+f"(d[47])
    : "r"(a0), "r"(a1), "r"(a2), "r"(a3), "l"(db), "r"(sc));
}
__device__ __forceinline__ void wgmma_rs_n256(float (&d)[128], uint32_t a0, uint32_t a1, uint32_t a2, uint32_t a3, uint64_t db, int sc) {
  asm volatile("{\n.reg .pred p;\nsetp.ne.b32 p, %133, 0;\n"
    "wgmma.mma_async.sync.aligned.m64n256k16.f32.bf16.bf16 {%0, %1, %2, %3, %4, %5, %6, %7, %8, %9, %10, %11, %12, %13, %14, %15, %16, %17, %18, %19, %20, %21, %22, %23, %24, %25, %26, %27, %28, %29, %30, %31, %32, %33, %34, %35, %36, %37, %38, %39, %40, %41, %42, %43, %44, %45, %46, %47, %48, %49, %50, %51, %52, %53, %54, %55, %56, %57, %58, %59, %60, %61, %62, %63, %64, %65, %66, %67, %68, %69, %70, %71, %72, %73, %74, %75, %76, %77, %78, %79, %80, %81, %82, %83, %84, %85, %86, %87, %88, %89, %90, %91, %92, %93, %94, %95, %96, %97, %98, %99, %100, %101, %102, %103, %104, %105, %106, %107, %108, %109, %110, %111, %112, %113, %114, %115, %116, %117, %118, %119, %120, %121, %122, %123, %124, %125, %126, %127}, {%128, %129, %130, %131}, %132, p, 1, 1, 1;\n}\n"
    : "+f"(d[0]), "+f"(d[1]), "+f"(d[2]), "+f"(d[3]), "+f"(d[4]), "+f"(d[5]), "+f"(d[6]), "+f"(d[7]), "+f"(d[8]), "+f"(d[9]), "+f"(d[10]), "+f"(d[11]), "+f"(d[12]), "+f"(d[13]), "+f"(d[14]), "+f"(d[15]), "+f"(d[16]), "+f"(d[17]), "+f"(d[18]), "+f"(d[19]), "+f"(d[20]), "+f"(d[21]), "+f"(d[22]), "+f"(d[23]), "+f"(d[24]), "+f"(d[25]), "+f"(d[26]), "+f"(d[27]), "+f"(d[28]), "+f"(d[29]), "+f"(d[30]), "+f"(d[31]), "+f"(d[32]), "+f"(d[33]), "+f"(d[34]), "+f"(d[35]), "+f"(d[36]), "+f"(d[37]), "+f"(d[38]), "+f"(d[39]), "+f"(d[40]), "+f"(d[41]), "+f"(d[42]), "+f"(d[43]), "+f"(d[44]), "+f"(d[45]), "+f"(d[46]), "+f"(d[47]), "+f"(d[48]), "+f"(d[49]), "+f"(d[50]), "+f"(d[51]), "+f"(d[52]), "+f"(d[53]), "+f"(d[54]), "+f"(d[55]), "+f"(d[56]), "+f"(d[57]), "+f"(d[58]), "+f"(d[59]), "+f"(d[60]), "+f"(d[61]), "+f"(d[62]), "+f"(d[63]), "+f"(d[64]), "+f"(d[65]), "+f"(d[66]), "+f"(d[67]), "+f"(d[68]), "+f"(d[69]), "+f"(d[70]), "+f"(d[71]), "+f"(d[72]), "+f"(d[73]), "+f"(d[74]), "+f"(d[75]), "+f"(d[76]), "+f"(d[77]), "+f"(d[78]), "+f"(d[79]), "+f"(d[80]), "+f"(d[81]), "+f"(d[82]), "+f"(d[83]), "+f"(d[84]), "+f"(d[85]), "+f"(d[86]), "+f"(d[87]), "+f"(d[88]), "+f"(d[89]), "+f"(d[90]), "+f"(d[91]), "+f"(d[92]), "+f"(d[93]), "+f"(d[94]), "+f"(d[95]), "+f"(d[96]), "+f"(d[97]), "+f"(d[98]), "+f"(d[99]), "+f"(d[100]), "+f"(d[101]), "+f"(d[102]), "+f"(d[103]), "+f"(d[104]), "+f"(d[105]), "+f"(d[106]), "+f"(d[107]), "+f"(d[108]), "+f"(d[109]), "+f"(d[110]), "+f"(d[111]), "+f"(d[112]), "+f"(d[113]), "+f"(d[114]), "+f"(d[115]), "+f"(d[116]), "+f"(d[117]), "+f"(d[118]), "+f"(d[119]), "+f"(d[120]), "+f"(d[121]), "+f"(d[122]), "+f"(d[123]), "+f"(d[124]), "+f"(d[125]), "+f"(d[126]), "+f"(d[127])
    : "r"(a0), "r"(a1), "r"(a2), "r"(a3), "l"(db), "r"(sc));
}
__device__ __forceinline__ void wgmma_rs_n112(float (&d)[56], uint32_t a0, uint32_t a1, uint32_t a2, uint32_t a3, uint64_t db, int sc) {
  asm volatile("{\n.reg .pred p;\nsetp.ne.b32 p, %61, 0;\n"
    "wgmma.mma_async.sync.aligned.m64n112k16.f32.bf16.bf16 {%0, %1, %2, %3, %4, %5, %6, %7, %8, %9, %10, %11, %12, %13, %14, %15, %16, %17, %18, %19, %20, %21, %22, %23, %24, %25, %26, %27, %28, %29, %30, %31, %32, %33, %34, %35, %36, %37, %38, %39, %40, %41, %42, %43, %44, %45, %46, %47, %48, %49, %50, %51, %52, %53, %54, %55}, {%56, %57, %58, %59}, %60, p, 1, 1, 1;\n}\n"
    : "+f"(d[0]), "+f"(d[1]), "+f"(d[2]), "+f"(d[3]), "+f"(d[4]), "+f"(d[5]), "+f"(d[6]), "+f"(d[7]), "+f"(d[8]), "+f"(d[9]), "+f"(d[10]), "+f"(d[11]), "+f"(d[12]), "+f"(d[13]), "+f"(d[14]), "+f"(d[15]), "+f"(d[16]), "+f"(d[17]), "+f"(d[18]), "+f"(d[19]), "+f"(d[20]), "+f"(d[21]), "+f"(d[22]), "+f"(d[23]), "+f"(d[24]), "+f"(d[25]), "+f"(d[26]), "+f"(d[27]), "+f"(d[28]), "+f"(d[29]), "+f"(d[30]), "+f"(d[31]), "+f"(d[32]), "+f"(d[33]), "+f"(d[34]), "+f"(d[35]), "+f"(d[36]), "+f"(d[37]), "+f"(d[38]), "+f"(d[39]), "+f"(d[40]), "+f"(d[41]), "+f"(d[42]), "+f"(d[43]), "+f"(d[44]), "+f"(d[45]), "+f"(d[46]), "+f"(d[47]), "+f"(d[48]), "+f"(d[49]), "+f"(d[50]), "+f"(d[51]), "+f"(d[52]), "+f"(d[53]), "+f"(d[54]), "+f"(d[55])
    : "r"(a0), "r"(a1), "r"(a2), "r"(a3), "l"(db), "r"(sc));
}

struct cplx { float re, im; };
__device__ __forceinline__ cplx cmul(cplx a, cplx b) {
  cplx r; r.re = a.re * b.re - a.im * b.im; r.im = a.re * b.im + a.im * b.re; return r;
}
__device__ __forceinline__ cplx zpow_acc(float a2, float bt, float c) {
  float mag = ex2f(a2 * c);
  float tr = bt * c;
  tr -= rintf(tr);
  float ang = tr * 6.283185307179586f;
  cplx r; r.re = mag * __cosf(ang); r.im = mag * __sinf(ang); return r;
}

constexpr int SB_TAB  = 0;
constexpr int SB_WREG = 7168;
constexpr int UZ = 40;
constexpr int SB_U    = 4 * SB_WREG;
constexpr int SB_KV   = SB_U + 172 * 36;
constexpr int SB_TOTAL = (SB_KV + 644 * 4 + 127) / 128 * 128;
constexpr int SB_F3   = 0;
constexpr int SB_F2   = 1792;
constexpr int SB_Y    = 4096;
constexpr int SB_KD   = SB_Y;
constexpr int SB_KDO  = SB_KD + 2240;
constexpr int FR_LN = 4 * SB_TOTAL;
constexpr int FR_CS = (FR_LN + LN_SMEM + 127) / 128 * 128;
constexpr int FR_X = FR_CS + CS_SMEM;
constexpr int FR_BAR = FR_X + 16384;
constexpr int FRONT_SMEM = FR_BAR + 16;

__device__ __forceinline__ int rowaddr(int r) { return 32 * r + 16 * (r >> 2); }
struct hc { __half2 re, im; };
__device__ __forceinline__ hc bcast(cplx a) { hc r; r.re = __float2half2_rn(a.re); r.im = __float2half2_rn(a.im); return r; }
__device__ __forceinline__ hc hmul(hc v, hc s) {
  hc r;
  r.re = __hfma2(v.re, s.re, __hneg2(__hmul2(v.im, s.im)));
  r.im = __hfma2(v.re, s.im, __hmul2(v.im, s.re));
  return r;
}
__device__ __forceinline__ uint32_t h2u(__half2 h) { return *reinterpret_cast<uint32_t*>(&h); }
__device__ __forceinline__ void gen8(unsigned char* p, cplx s, cplx r1, hc r1sq, hc r2) {
  const cplx v1 = cmul(s, r1);
  hc p0; p0.re = __floats2half2_rn(s.re, v1.re); p0.im = __floats2half2_rn(s.im, v1.im);
  const hc p1 = hmul(p0, r1sq), p2 = hmul(p0, r2), p3 = hmul(p1, r2);
  *reinterpret_cast<uint4*>(p) = make_uint4(h2u(p0.re), h2u(p1.re), h2u(p2.re), h2u(p3.re));
  *reinterpret_cast<uint4*>(p + 8 * 112) = make_uint4(h2u(p0.im), h2u(p1.im), h2u(p2.im), h2u(p3.im));
}
__device__ __forceinline__ cplx csq(cplx a) { cplx r; r.re = a.re * a.re - a.im * a.im; r.im = 2.f * a.re * a.im; return r; }
__device__ __forceinline__ cplx cconj(cplx a) { a.im = -a.im; return a; }
__device__ __forceinline__ uint2 lds64(uint32_t a) { uint2 r; asm volatile("ld.shared.v2.u32 {%0,%1}, [%2];" : "=r"(r.x), "=r"(r.y) : "r"(a)); return r; }

__global__ void __launch_bounds__(512, 1) k_ssm(const bf16* __restrict__ Are, const bf16* __restrict__ Aim,
                                             const bf16* __restrict__ Bre, const bf16* __restrict__ Bim,
                                             const bf16* __restrict__ Cre, const bf16* __restrict__ Cim,
                                             const bf16* __restrict__ log_dt, const bf16* __restrict__ Dskip,
                                             const bf16* __restrict__ x, const bf16* __restrict__ wg,
                                             const bf16* __restrict__ wu, const bf16* __restrict__ wd,
                                             const __grid_constant__ CUtensorMap tmU, const __grid_constant__ CUtensorMap tmX) {
  pdl_launch();
  TS_MIN(0); TS_MAX(1);
#define TPW ((int)(blockIdx.x & 1) * 8 + 1)
  TP_INIT(0);
  extern __shared__ __align__(1024) unsigned char smem_all[];
  const int sub = threadIdx.x >> 7;
  const int tid = threadIdx.x & 127, lane = tid & 31;
  const int bar = 1 + sub;
  unsigned char* sm = smem_all + sub * SB_TOTAL;
  const uint32_t sbase = smem_u32(sm);
  const int w = ((tid >> 5) + sub) & 3;
  const int g = lane >> 2, t = lane & 3;
  const bool upper = threadIdx.x >= 256;
  const int hbar = upper ? 14 : 13;
  const bool do_ln = upper && blockIdx.x < 128;
  if (do_ln) ln1_load(x, blockIdx.x, smem_all + FR_LN);
  if (blockIdx.x >= 112) {
    if (do_ln) ln1_tile(blockIdx.x, smem_all + FR_LN);
    for (int i = (blockIdx.x - 112) * 512 + threadIdx.x; i < FF * DM * 2 / 128; i += 20 * 512)
      asm volatile("prefetch.global.L2 [%0];" ::"l"(reinterpret_cast<const char*>(wd) + (size_t)i * 128));
    return;
  }
  const int d = blockIdx.x * 4 + sub;
  const int pidx = (d * NM + 64 * w) / 2 + lane;
  const uint32_t pAre = __ldg(reinterpret_cast<const uint32_t*>(Are) + pidx), pAim = __ldg(reinterpret_cast<const uint32_t*>(Aim) + pidx);
  const uint32_t pBre = __ldg(reinterpret_cast<const uint32_t*>(Bre) + pidx), pBim = __ldg(reinterpret_cast<const uint32_t*>(Bim) + pidx);
  const uint32_t pCre = __ldg(reinterpret_cast<const uint32_t*>(Cre) + pidx), pCim = __ldg(reinterpret_cast<const uint32_t*>(Cim) + pidx);
  const float dt = bf16r(expf(__bfloat162float(log_dt[d])));
  const uint32_t dsk2 = (uint32_t)__bfloat16_as_ushort(Dskip[d]) * 0x10001u;
  if (upper) ln1_tile(blockIdx.x, smem_all + FR_LN);
  TS_MIN(2); TS_MAX(3);
  if (tid < 90) *reinterpret_cast<uint4*>(sm + SB_U + tid * 16) = make_uint4(0, 0, 0, 0);
  if (tid >= 96 && tid < 105) *reinterpret_cast<uint4*>(sm + SB_U + 168 * 36 + (tid - 96) * 16) = make_uint4(0, 0, 0, 0);
  float w0re, w0im, w1re, w1im;
  {
    const float br0 = dt * bflo(pBre), bi0 = dt * bflo(pBim), br1 = dt * bfhi(pBre), bi1 = dt * bfhi(pBim);
    w0re = bflo(pCre) * br0 - bflo(pCim) * bi0; w0im = bflo(pCre) * bi0 + bflo(pCim) * br0;
    w1re = bfhi(pCre) * br1 - bfhi(pCim) * bi1; w1im = bfhi(pCre) * bi1 + bfhi(pCim) * br1;
  }
  float mx = fmaxf(fmaxf(fabsf(w0re), fabsf(w0im)), fmaxf(fabsf(w1re), fabsf(w1im)));
#pragma unroll
  for (int o = 16; o > 0; o >>= 1) mx = fmaxf(mx, __shfl_xor_sync(0xffffffffu, mx, o));
  int ex = (__float_as_uint(mx) >> 23) & 0xff;
  ex = min(max(ex, 1), 252);
  const float scale = __uint_as_float((uint32_t)(253 - ex) << 23);
  const float inv_scale = __uint_as_float((uint32_t)(ex + 1) << 23);

  TP(1, 1);
  float acc[5][4];
#pragma unroll
  for (int i = 0; i < 5; i++) { acc[i][0] = acc[i][1] = acc[i][2] = acc[i][3] = 0.f; }
  float k2048 = 0.f;
  unsigned char* tabw = sm + SB_TAB + w * SB_WREG;
  const uint32_t ldA = sbase + SB_TAB + w * SB_WREG + ((lane & 7) + 8 * ((lane >> 4) & 1)) * 112 + ((lane >> 3) & 1) * 16;
  const uint32_t ldB = sbase + SB_TAB + w * SB_WREG + ((lane & 7) + 8 * ((lane >> 3) & 1)) * 112 + 32 + (lane >> 4) * 16;
#pragma unroll 1
  for (int r = 0; r < 2; r++) {
    {
      const float a2 = dt * (r ? bfhi(pAre) : bflo(pAre)) * 1.4426950408889634f;
      const float bt = dt * (r ? bfhi(pAim) : bflo(pAim)) * 0.15915494309189535f;
      cplx W; W.re = (r ? w1re : w0re) * scale; W.im = -(r ? w1im : w0im) * scale;
      unsigned char* rec = tabw + ((lane >> 3) * 16 + (lane & 7)) * 112;
      const cplx y1 = zpow_acc(a2, -bt, 1.f), z8 = zpow_acc(a2, bt, 8.f), y128 = zpow_acc(a2, -bt, 128.f);
      const cplx y512 = zpow_acc(a2, -bt, 512.f), y1024 = zpow_acc(a2, -bt, 1024.f);
      const cplx z16 = csq(z8), z32 = csq(z16), z64 = csq(z32);
      const cplx y2 = csq(y1), y4 = csq(y2), y256 = csq(y128);
      cplx one; one.re = 1.f; one.im = 0.f;
      const hc h16 = bcast(z16), h32 = bcast(z32), h2 = bcast(y2), h4 = bcast(y4);
      const hc h128 = bcast(y128), h256 = bcast(y256), h512 = bcast(y512);
      gen8(rec, one, z8, h16, h32);
      gen8(rec + 16, z64, z8, h16, h32);
      gen8(rec + 32, W, y1, h2, h4);
      gen8(rec + 48, cmul(W, y128), y1, h2, h4);
      gen8(rec + 64, cmul(W, y256), y2, h4, h128);
      gen8(rec + 80, cmul(W, y512), y128, h256, h4);
      const cplx w1024 = cmul(W, y1024);
      gen8(rec + 96, w1024, y128, h256, h512);
      k2048 += w1024.re * y1024.re - w1024.im * y1024.im;
    }
    __syncwarp();
#pragma unroll
    for (int ks = 0; ks < 4; ks++) {
      uint32_t a0, a1, a2, a3, b0, b1, b2, b3;
      ldsm_x4_t(ldA + ks * 1792, a0, a1, a2, a3);
      ldsm_x4_t(ldB + ks * 1792, b0, b1, b2, b3);
      mma_f16(acc[0], a0, a1, a2, a3, b0, b1);
      mma_f16(acc[1], a0, a1, a2, a3, b2, b3);
      ldsm_x4_t(ldB + ks * 1792 + 32, b0, b1, b2, b3);
      mma_f16(acc[2], a0, a1, a2, a3, b0, b1);
      mma_f16(acc[3], a0, a1, a2, a3, b2, b3);
      ldsm_x2_t(ldB + ks * 1792 + 64, b0, b1);
      mma_f16(acc[4], a0, a1, a2, a3, b0, b1);
    }
    __syncwarp();
  }
  TP(1, 2);
  {
    float* red = reinterpret_cast<float*>(tabw);
#pragma unroll
    for (int hr = 0; hr < 2; hr++) {
      const int row = g + 8 * hr;
      *reinterpret_cast<float2*>(red + 8 * row + 2 * t) = make_float2(acc[0][2 * hr] * inv_scale, acc[0][2 * hr + 1] * inv_scale);
      *reinterpret_cast<float2*>(red + 128 + 8 * row + 2 * t) = make_float2(acc[1][2 * hr] * inv_scale, acc[1][2 * hr + 1] * inv_scale);
      *reinterpret_cast<float2*>(red + 256 + 64 * (t >> 1) + 2 * (t & 1) + 4 * row) = make_float2(acc[2][2 * hr] * inv_scale, acc[2][2 * hr + 1] * inv_scale);
      red[384 + 64 * (t & 1) + (t >> 1) + 2 * row] = acc[3][2 * hr] * inv_scale;
      red[384 + 64 * (t & 1) + 32 + (t >> 1) + 2 * row] = acc[3][2 * hr + 1] * inv_scale;
      red[512 + 32 * t + row] = acc[4][2 * hr] * inv_scale;
      red[512 + 32 * t + 16 + row] = acc[4][2 * hr + 1] * inv_scale;
    }
#pragma unroll
    for (int o = 16; o > 0; o >>= 1) k2048 += __shfl_xor_sync(0xffffffffu, k2048, o);
    if (lane == 0) red[640] = k2048 * inv_scale;
  }
  TP(1, 3);
  const uint32_t ubar = smem_u32(smem_all) + FR_BAR + (upper ? 8 : 0);
  const int ustg = upper ? FR_LN : FR_CS;
  if ((threadIdx.x & 255) == 0) {
    mbar_init(ubar, 1);
    asm volatile("fence.mbarrier_init.release.cluster;" ::: "memory");
    flag_wait(&g_cnt[7], (__ldcg(&g_epoch) + 1u) * 128u);
    asm volatile("fence.proxy.async;" ::: "memory");
    mbar_expect(ubar, 16384);
    tma2d(smem_u32(smem_all) + ustg, &tmU, ubar, (blockIdx.x * 4 + (sub & 2)) * 16, 0);
    tma2d(smem_u32(smem_all) + FR_X + (upper ? 8192 : 0), &tmX, ubar, (blockIdx.x * 4 + (sub & 2)) * 16, 0);
  }
  __syncwarp();
  named_bar(bar, 128);
  TP(1, 6);
  float* Kv = reinterpret_cast<float*>(sm + SB_KV);
  {
    const float* r0 = reinterpret_cast<const float*>(sm + SB_TAB);
    constexpr int WS = SB_WREG / 4;
    const float4 a = *reinterpret_cast<const float4*>(r0 + 4 * tid), b = *reinterpret_cast<const float4*>(r0 + WS + 4 * tid);
    const float4 c = *reinterpret_cast<const float4*>(r0 + 2 * WS + 4 * tid), e = *reinterpret_cast<const float4*>(r0 + 3 * WS + 4 * tid);
    *reinterpret_cast<float4*>(Kv + 4 * tid) =
        make_float4((a.x + b.x) + (c.x + e.x), (a.y + b.y) + (c.y + e.y), (a.z + b.z) + (c.z + e.z), (a.w + b.w) + (c.w + e.w));
    const int i = 512 + tid;
    Kv[i] = (r0[i] + r0[WS + i]) + (r0[2 * WS + i] + r0[3 * WS + i]);
    if (tid == 0) Kv[640] = (r0[640] + r0[WS + 640]) + (r0[2 * WS + 640] + r0[3 * WS + 640]);
  }
  named_bar(bar, 128);
  TP(1, 4);
  {
    auto tap_idx = [](int j) { const int m = j >> 1; const int r = (j & 1) ? m + (m & 1) : m; return min(max(j < 256 ? j : 128 + r, 0), 640); };
    float kd[3][3], f3[3], f2[3];
#pragma unroll
    for (int it = 0; it < 3; it++) {
      const int j = 528 - 2 * (tid + 128 * it);
#pragma unroll
      for (int e = 0; e < 3; e++) kd[it][e] = Kv[tap_idx(j + 1 - e)];
    }
    const int fa = tid >= 48, xa = tid - 48 * fa, ja = 144 - 2 * xa;
    const int fb = tid >> 6, xb = tid & 63, jb = 160 - 2 * xb;
#pragma unroll
    for (int e = 0; e < 3; e++) {
      f3[e] = Kv[min(max(384 + fa + 2 * (ja + 1 - e), 0), 640)];
      f2[e] = Kv[min(256 + fb + 2 * (jb + 1 - e), 640)];
    }
    const float k512 = Kv[384];
    uint32_t* ee = reinterpret_cast<uint32_t*>(sm + SB_KD);
#pragma unroll
    for (int it = 0; it < 3; it++) {
      const int x = tid + 128 * it, j = 528 - 2 * x;
      const float k0 = (j >= -1 && j <= 508) ? kd[it][0] : 0.f;
      float k1 = (j >= 0 && j <= 510) ? kd[it][1] : 0.f;
      const float k2 = (j >= 1 && j <= 510) ? kd[it][2] : 0.f;
      if (j == 510) k1 -= k512;
      const uint32_t we = pack_bf16(k1, k2), wo = pack_bf16(k0, k1);
      if (x < 272) { ee[2 * x] = we; ee[560 + 2 * x] = wo; }
      if (x < 272 && x >= 4) { ee[2 * x - 7] = we; ee[560 + 2 * x - 7] = wo; }
    }
    {
      const int hi = 128 - fa;
      const float k0 = (ja + 1 >= 64 && ja + 1 <= hi) ? f3[0] : 0.f, k1 = (ja >= 64 && ja <= hi) ? f3[1] : 0.f;
      const float k2 = (ja - 1 >= 64 && ja - 1 <= hi) ? f3[2] : 0.f;
      const uint32_t we = pack_bf16(k1, k2), wo = pack_bf16(k0, k1);
      uint32_t* p = reinterpret_cast<uint32_t*>(sm + SB_F3) + fa * 224;
      if (tid < 96) { p[2 * xa] = we; p[112 + 2 * xa] = wo; }
      if (tid < 96 && xa < 44) { p[2 * xa + 9] = we; p[112 + 2 * xa + 9] = wo; }
    }
    {
      const float k0 = (jb + 1 >= 64 && jb + 1 <= 127) ? f2[0] : 0.f, k1 = (jb >= 64 && jb <= 127) ? f2[1] : 0.f;
      const float k2 = (jb - 1 >= 64 && jb - 1 <= 127) ? f2[2] : 0.f;
      const uint32_t we = pack_bf16(k1, k2), wo = pack_bf16(k0, k1);
      uint32_t* p = reinterpret_cast<uint32_t*>(sm + SB_F2) + fb * 288;
      p[2 * xb] = we; p[144 + 2 * xb] = wo;
      p[2 * xb + 17] = we; p[144 + 2 * xb + 17] = wo;
    }
  }
  const float k1024 = Kv[512];
  named_bar(hbar, 256);
  mbar_wait(ubar, 0);
#pragma unroll
  for (int k = 0; k < 2; k++) {
    const int c = tid + 128 * k;
    *reinterpret_cast<uint4*>(sm + SB_U + rowaddr((c >> 1) + UZ) + (c & 1) * 16) =
        *reinterpret_cast<const uint4*>(smem_all + ustg + (c >> 1) * 64 + (sub & 1) * 32 + (c & 1) * 16);
  }
  named_bar(hbar, 256);
  if (!upper) colsum_load(wg, wu, blockIdx.x, smem_all + FR_CS);
  TP(1, 5);
  const int krow = (lane & 7) + 8 * ((lane >> 3) & 1);
  if (w < 2) {
    float acd[4][2][4];
#pragma unroll
    for (int c = 0; c < 4; c++)
#pragma unroll
      for (int i = 0; i < 2; i++)
#pragma unroll
        for (int e = 0; e < 4; e++) acd[c][i][e] = 0.f;
    const uint32_t aQ = sbase + SB_U + rowaddr(UZ + 64 * w + 4 * krow) + (lane >> 4) * 16;
    const uint32_t pb = sbase + ((g & 1) ? SB_KDO + ((529 - g) / 2 + t) * 8 : SB_KD + ((528 - g) / 2 + t) * 8);
    uint32_t Q[36][4];
#define QOFF(j) (32 * (j) + 16 * (((j) + 64) / 4 - 16))
#pragma unroll
    for (int n = 0; n < 5; n++) ldsm_x4(aQ + QOFF(3 - n), Q[n][0], Q[n][1], Q[n][2], Q[n][3]);
#pragma unroll
    for (int q = 0; q < 33; q++) {
      if (q + 5 < 36) ldsm_x4(aQ + QOFF(3 - (q + 5)), Q[q + 5][0], Q[q + 5][1], Q[q + 5][2], Q[q + 5][3]);
      const uint2 e0 = lds64(pb - 32 * (2 * q));
      const uint2 e1 = lds64(pb - 32 * (2 * q + 1));
#pragma unroll
      for (int c = 0; c < 4; c++) {
        mma_bf16(acd[c][0], Q[3 - c + q][0], Q[3 - c + q][1], Q[3 - c + q][2], Q[3 - c + q][3], e0.x, e0.y);
        mma_bf16(acd[c][1], Q[3 - c + q][0], Q[3 - c + q][1], Q[3 - c + q][2], Q[3 - c + q][3], e1.x, e1.y);
      }
    }
#undef QOFF
    const int yl = (64 * (16 * w + g) + 2 * t + 16 * (g & 1) + 8 * ((g >> 1) & 1)) * 4;
    unsigned char* yb = sm + SB_Y + 8192;
#pragma unroll
    for (int c = 0; c < 4; c++)
#pragma unroll
      for (int nu = 0; nu < 2; nu++)
#pragma unroll
        for (int hr = 0; hr < 2; hr++)
          *reinterpret_cast<float2*>(yb + ((yl ^ ((16 * c + 8 * (nu ^ (c >> 1))) * 4)) + hr * 2048)) = make_float2(acd[c][nu][2 * hr], acd[c][nu][2 * hr + 1]);
  } else {
    const int yl = (16 * (g ^ ((g >> 2) & 1)) + 2 * t + 8 * ((g >> 1) & 1)) * 4;
    if (w == 2) {
      float ac[7][2][4];
#pragma unroll
      for (int T = 0; T < 7; T++)
#pragma unroll
        for (int i = 0; i < 2; i++)
#pragma unroll
          for (int e = 0; e < 4; e++) ac[T][i][e] = 0.f;
      uint32_t BA[2][4];
#pragma unroll
      for (int ks = 0; ks < 2; ks++)
#pragma unroll
        for (int r = 0; r < 4; r++) {
          uint32_t v = 0;
#pragma unroll
          for (int e = 0; e < 2; e++) {
            const int dlt = (2 * t + e + 8 * (r >> 1) + 16 * ks - 8) - g;
            const bool on = (r & 1) ? (dlt >= -5 && dlt <= -3) : (dlt >= -2 && dlt <= 2);
            v |= on ? (0x3f80u << (16 * e)) : 0u;
          }
          BA[ks][r] = v;
        }
      const int chl = 2 * UZ + (lane & 7) + (lane >> 3) - 1;
      const uint32_t ub = sbase + SB_U + rowaddr(chl >> 1) + (chl & 1) * 16;
      const uint32_t fb = sbase + SB_F2 + (80 - (g - t)) * 8;
#pragma unroll
      for (int sp = 0; sp < 2; sp++) {
        uint32_t bb[2][7][2];
#pragma unroll
        for (int i = 0; i < 7 - sp; i++) {
          const int beta = 11 - sp - 2 * i;
#pragma unroll
          for (int o = 0; o < 2; o++) {
            uint32_t u0, u1, u2, u3;
            ldsm_x4(ub + (2 * beta + o) * 144, u0, u1, u2, u3);
            float z[4] = {0.f, 0.f, 0.f, 0.f};
            mma_bf16(z, BA[0][0], BA[0][1], BA[0][2], BA[0][3], u0, u1);
            mma_bf16(z, BA[1][0], BA[1][1], BA[1][2], BA[1][3], u2, u3);
            bb[0][i][o] = pack_bf16(z[0], z[1]);
            bb[1][i][o] = pack_bf16(z[2], z[3]);
          }
        }
#pragma unroll
        for (int f = 0; f < 2; f++) {
#pragma unroll
          for (int k = 0; k < 3; k++) {
#pragma unroll
            for (int nu = 0; nu < 2; nu++) {
              const uint2 A01 = lds64(fb + f * 1152 + nu * 576 - 32 * (6 + 2 * (2 * k + sp)));
              const uint2 A23 = lds64(fb + f * 1152 + nu * 576 - 32 * (5 + 2 * (2 * k + sp)));
#pragma unroll
              for (int i = 0; i < 7 - sp; i++) {
                const int T = 7 - i + k;
                if (T <= 7) mma_bf16(ac[T - 1][nu], A01.x, A01.y, A23.x, A23.y, bb[f][i][0], bb[f][i][1]);
              }
            }
          }
        }
      }
      named_bar(5 + bar, 96);
      unsigned char* yb = sm + SB_Y;
#pragma unroll
      for (int T = 0; T <= 7; T++)
#pragma unroll
        for (int nu = 0; nu < 2; nu++)
#pragma unroll
          for (int hr = 0; hr < 2; hr++)
            *reinterpret_cast<float2*>(yb + ((yl ^ ((8 * (nu ^ hr)) * 4)) + (16 * T + 8 * hr) * 64)) =
                T ? make_float2(ac[T ? T - 1 : 0][nu][2 * hr], ac[T ? T - 1 : 0][nu][2 * hr + 1]) : make_float2(0.f, 0.f);
    } else {
      float ac[5][2][4];
#pragma unroll
      for (int T = 0; T < 5; T++)
#pragma unroll
        for (int i = 0; i < 2; i++)
#pragma unroll
          for (int e = 0; e < 4; e++) ac[T][i][e] = 0.f;
      const uint32_t fb = sbase + SB_F3 + ((g & 1) ? 448 + ((145 - g) / 2 + t) * 8 : ((144 - g) / 2 + t) * 8);
      uint32_t ur[3];
#pragma unroll
      for (int sg = 0; sg < 3; sg++) ur[sg] = sbase + SB_U + rowaddr(UZ + (lane & 7) + 8 * (lane >> 4) + sg - 1) + ((lane >> 3) & 1) * 16;
#pragma unroll 1
      for (int f = 0; f < 2; f++) {
        uint32_t BA[3][4];
        const int lo = f ? -11 : -4, hi = f ? -5 : 4;
#pragma unroll
        for (int sg = 0; sg < 3; sg++)
#pragma unroll
          for (int r = 0; r < 4; r++) {
            uint32_t v = 0;
#pragma unroll
            for (int e = 0; e < 2; e++) {
              const int dlt = (2 * t + e + 8 * (r >> 1) + 16 * (sg - 1)) - (g + 8 * (r & 1));
              v |= (dlt >= lo && dlt <= hi) ? (0x3f80u << (16 * e)) : 0u;
            }
            BA[sg][r] = v;
          }
        uint2 A01[5], A23[5];
#pragma unroll
        for (int s = 0; s < 5; s++) {
          A01[s] = lds64(fb + f * 896 - 32 * (8 + 2 * s));
          A23[s] = lds64(fb + f * 896 - 32 * (7 + 2 * s));
        }
#pragma unroll
        for (int beta = 3; beta >= -1; beta--) {
          float z0[4] = {0.f, 0.f, 0.f, 0.f}, z1[4] = {0.f, 0.f, 0.f, 0.f};
#pragma unroll
          for (int sg = 0; sg < 3; sg++) {
            uint32_t u0, u1, u2, u3;
            ldsm_x4(ur[sg] + beta * 576, u0, u1, u2, u3);
            mma_bf16(z0, BA[sg][0], BA[sg][1], BA[sg][2], BA[sg][3], u0, u1);
            mma_bf16(z1, BA[sg][0], BA[sg][1], BA[sg][2], BA[sg][3], u2, u3);
          }
          const uint32_t b0 = pack_bf16(z0[0], z0[1]), b1 = pack_bf16(z1[0], z1[1]);
          const uint32_t b2 = pack_bf16(z0[2], z0[3]), b3 = pack_bf16(z1[2], z1[3]);
#pragma unroll
          for (int s = 0; s < 5; s++) {
            const int T = beta + 4 + s;
            if (T <= 7) {
              mma_bf16(ac[T - 3][0], A01[s].x, A01[s].y, A23[s].x, A23[s].y, b0, b1);
              mma_bf16(ac[T - 3][1], A01[s].x, A01[s].y, A23[s].x, A23[s].y, b2, b3);
            }
          }
        }
      }
      {
        const uint32_t nk = (uint32_t)__bfloat16_as_ushort(__float2bfloat16_rn(-k1024));
        uint32_t PC[5];
#pragma unroll
        for (int m = 0; m < 5; m++) {
          const int j = 8 * (125 + m) + g - 2 * t;
          PC[m] = ((j == 1020 || j == 1021) ? nk : 0u) | ((j == 1021 || j == 1022) ? (nk << 16) : 0u);
        }
#pragma unroll
        for (int k = 0; k < 2; k++) {
          const uint32_t ab = sbase + SB_U + rowaddr(UZ + 48 - 63 - k + krow) + (lane >> 4) * 16;
#pragma unroll
          for (int T = 3; T <= 7; T++) {
            uint32_t a0, a1, a2, a3;
            ldsm_x4(ab + (T - 3) * 576, a0, a1, a2, a3);
            mma_bf16(ac[T - 3][0], a0, a1, a2, a3, PC[1 + 2 * k], PC[2 * k]);
            mma_bf16(ac[T - 3][1], a0, a1, a2, a3, PC[2 + 2 * k], PC[1 + 2 * k]);
          }
        }
      }
      unsigned char* yb = sm + SB_Y + 16384;
#pragma unroll
      for (int T = 0; T <= 7; T++)
#pragma unroll
        for (int nu = 0; nu < 2; nu++)
#pragma unroll
          for (int hr = 0; hr < 2; hr++)
            *reinterpret_cast<float2*>(yb + ((yl ^ ((8 * (nu ^ hr)) * 4)) + (16 * T + 8 * hr) * 64)) =
                T >= 3 ? make_float2(ac[T >= 3 ? T - 3 : 0][nu][2 * hr], ac[T >= 3 ? T - 3 : 0][nu][2 * hr + 1]) : make_float2(0.f, 0.f);
    }
  }
  if (w < 2) asm volatile("bar.arrive %0, 96;" ::"r"(5 + bar) : "memory");
  TP(1, 7);
  named_bar(bar, 128);
  TP(1, 8);
  {
    const __nv_bfloat162 ds = *reinterpret_cast<const __nv_bfloat162*>(&dsk2);
    const int r0 = tid >> 2, ch = tid & 3;
    const int yo = (16 * (r0 ^ ((r0 >> 2) & 1)) + ((4 * ch) ^ (8 * (((r0 >> 1) ^ (r0 >> 3)) & 1)))) * 4;
    const int uo = SB_U + rowaddr(r0 + UZ) + ch * 8;
#pragma unroll
    for (int k = 0; k < 4; k++) {
      const float4 a = *reinterpret_cast<const float4*>(sm + SB_Y + yo + k * 2048);
      const float4 b = *reinterpret_cast<const float4*>(sm + SB_Y + 8192 + yo + k * 2048);
      const float4 c = *reinterpret_cast<const float4*>(sm + SB_Y + 16384 + yo + k * 2048);
      const uint2 uw = *reinterpret_cast<const uint2*>(sm + uo + k * 1152);
      const uint2 xw = *reinterpret_cast<const uint2*>(smem_all + FR_X + (sub >> 1) * 8192 + r0 * 64 + (sub & 1) * 32 + ch * 8 + k * 2048);
      const uint32_t y0 = pack_bf16(b.x + (a.x + c.x), b.y + (a.y + c.y)), y1 = pack_bf16(b.z + (a.z + c.z), b.w + (a.w + c.w));
      const __nv_bfloat162 h0 = __hadd2_rn(*reinterpret_cast<const __nv_bfloat162*>(&xw.x),
          __hadd2_rn(*reinterpret_cast<const __nv_bfloat162*>(&y0), __hmul2_rn(*reinterpret_cast<const __nv_bfloat162*>(&uw.x), ds)));
      const __nv_bfloat162 h1 = __hadd2_rn(*reinterpret_cast<const __nv_bfloat162*>(&xw.y),
          __hadd2_rn(*reinterpret_cast<const __nv_bfloat162*>(&y1), __hmul2_rn(*reinterpret_cast<const __nv_bfloat162*>(&uw.y), ds)));
      *reinterpret_cast<uint2*>(g_hT + (size_t)d * SEQ + tid * 4 + k * 512) =
          make_uint2(*reinterpret_cast<const uint32_t*>(&h0), *reinterpret_cast<const uint32_t*>(&h1));
    }
  }
  if (!upper) {
    cp_async_wait_all();
    named_bar(hbar, 256);
    colsum_reduce(smem_all + FR_CS);
    named_bar(hbar, 256);
    if (threadIdx.x < 32) colsum_store(blockIdx.x, smem_all + FR_CS);
  }
  named_bar(hbar, 256);
  if ((threadIdx.x & 255) == 0) {
    __threadfence();
    asm volatile("red.relaxed.gpu.global.add.u32 [%0], 1;" ::"l"(&g_cnt[blockIdx.x >> 4]) : "memory");
  }
  TP(1, 10);
  TP_DUMP(0);
#undef TPW
}

constexpr int M_A     = 0;
constexpr int M_W     = 7 * 16384;
constexpr int M_XB    = M_W + 3 * 32768;
constexpr int M_CS    = M_XB + 14336;
constexpr int M_BAR   = M_CS + 1792;
constexpr int M_TOTAL = M_BAR + 384;

__device__ __forceinline__ float sigmoid_fast(float x) {
  float th; asm("tanh.approx.f32 %0, %1;" : "=f"(th) : "f"(0.5f * x));
  return fmaf(0.5f, th, 0.5f);
}
template <int NCB, int NA, int OFS>
__device__ __forceinline__ void g1_pack(const float (&acc)[NA], uint32_t* pk, const float* cs,
                                        float mb0, float rs0, float mb1, float rs1, int lane) {
  const int t = lane & 3;
  const float c0 = -mb0 * rs0, c1 = -mb1 * rs1;
#pragma unroll
  for (int cb = 0; cb < NCB; cb++) {
    const float2 sc = *reinterpret_cast<const float2*>(cs + cb * 8 + 2 * t);
    pk[2 * cb]     = pack_bf16(fmaf(acc[OFS + 4 * cb + 0], rs0, c0 * sc.x), fmaf(acc[OFS + 4 * cb + 1], rs0, c0 * sc.y));
    pk[2 * cb + 1] = pack_bf16(fmaf(acc[OFS + 4 * cb + 2], rs1, c1 * sc.x), fmaf(acc[OFS + 4 * cb + 3], rs1, c1 * sc.y));
  }
}
__device__ __forceinline__ uint32_t glu2(uint32_t gw, uint32_t uw) {
  return pack_bf16(sigmoid_fast(bflo(gw)) * bflo(uw), sigmoid_fast(bfhi(gw)) * bfhi(uw));
}
__device__ __forceinline__ uint32_t w2_slot(int j, int kp) {
  const int sl = j % 10;
  if (sl < 6) return M_W + ((sl >> 1) + 2) % 3 * 32768 + (sl & 1) * 16384;
  const int i = sl - 6;
  return M_A + (i + (i >= kp ? 3 : 0)) * 16384;
}

__global__ void __cluster_dims__(2, 1, 1) __launch_bounds__(384, 1)
k_mlp(const __grid_constant__ CUtensorMap tmA, const __grid_constant__ CUtensorMap tmG,
      const __grid_constant__ CUtensorMap tmU, const __grid_constant__ CUtensorMap tmD, bf16* __restrict__ out) {
  extern __shared__ __align__(1024) unsigned char smem[];
  const uint32_t sb = smem_u32(smem);
  const int tid = threadIdx.x, lane = tid & 31, warp = tid >> 5;
  const uint32_t rank = blockIdx.x & 1;
  const int pr = blockIdx.x >> 1;
  const int mt = pr & 15;
  const int fp = pr >> 4;
  const int fj = 4 * rank + fp;
  const int kp = min((112 * fp) >> 6, 4);
  const uint32_t barA = sb + M_BAR, barF = barA + 56, barE = barF + 24, barS = barE + 24;
  const uint32_t barW2 = barS + 8, barAf = barW2 + 112, barX = barAf + 8, barH = barX + 8, barE2 = barH + 16;
  TP_INIT(1);
  if (tid == 288 || tid == 289) prefetch_tm(tid == 288 ? &tmA : &tmD);
  if (lane == 0 && warp < 5) {
#pragma unroll
    for (int i = 0; i < 8; i++) {
      const int b = warp * 8 + i;
      if (b < 36 && (b < 7 || b >= 10)) mbar_init(barA + 8 * b, ((b >= 10 && b < 13) || b == 28 || b >= 32) ? 2 : (b == 29 ? 4 : 1));
    }
    asm volatile("fence.mbarrier_init.release.cluster;" ::: "memory");
    if (sb & 1023) __trap();
  }
  if (tid == 256) {
    for (int s = 0; s < 3; s++) mbar_init(barF + 8 * s, 1);
    asm volatile("fence.mbarrier_init.release.cluster;" ::: "memory");
    for (int s = 0; s < 3; s++) {
      mbar_expect(barF + 8 * s, 32768);
      const uint32_t dst = sb + M_W + s * 32768;
      tma2d(dst, &tmG, barF + 8 * s, 224 * fj, 64 * s);
      tma2d(dst + 16384, &tmU, barF + 8 * s, 224 * fj, 64 * s);
      tma2d(dst + 8192, &tmG, barF + 8 * s, 224 * fj + 64, 64 * s);
      tma2d(dst + 24576, &tmU, barF + 8 * s, 224 * fj + 64, 64 * s);
    }
  }
  __syncthreads();
  if (tid == 0) TQ(0);
  cluster_arrive();

  if (warp >= 8) {
    const unsigned int ep = __ldcg(&g_epoch);
    asm volatile("setmaxnreg.dec.sync.aligned.u32 24;");
    if (warp == 8) {
      if (lane == 0) {
        TQ(2);
        for (int it = 3; it < 14; it++) {
          const int s = it % 3, rnd = it / 3;
          const bool pb = it >= 7;
          const int kb = pb ? it - 7 : it;
          if (rnd > 0) mbar_wait(barE + 8 * s, (rnd - 1) & 1);
          mbar_expect(barF + 8 * s, 32768);
          const uint32_t dst = sb + M_W + s * 32768;
          const int c0 = 224 * fj + (pb ? 128 : 0);
          tma2d(dst, &tmG, barF + 8 * s, c0, 64 * kb);
          tma2d(dst + 16384, &tmU, barF + 8 * s, c0, 64 * kb);
          tma2d(dst + 8192, &tmG, barF + 8 * s, c0 + 64, 64 * kb);
          tma2d(dst + 24576, &tmU, barF + 8 * s, c0 + 64, 64 * kb);
        }
        for (int j = 0; j < 14; j++) {
          if (j < 6 && !(j & 1)) { const int it = 11 + (j >> 1); mbar_wait(barE + 8 * (it % 3), (it / 3) & 1); }
          if (j == 6) mbar_wait(barAf, 0);
          if (j >= 10) mbar_wait(barE2 + 8 * (j - 10), 0);
          mbar_expect(barW2 + 8 * j, 16384);
          const uint32_t dst = sb + w2_slot(j, kp);
#pragma unroll
          for (int h = 0; h < 2; h++) {
            const int u = 2 * j + h;
            int c, o;
            if (u < 7) { c = 0; o = u; } else if (u < 19) { c = 1 + (u - 7) / 4; o = (u - 7) % 4; } else { c = 1 + (u - 19) / 3; o = 4 + (u - 19) % 3; }
            const int row = (4 * rank + ((fp + c) & 3)) * 224 + 32 * o;
            tma2d(dst + h * 4096, &tmD, barW2 + 8 * j, 112 * fp, row);
            tma2d(dst + 8192 + h * 4096, &tmD, barW2 + 8 * j, 112 * fp + 64, row);
          }
        }
      }
      __syncwarp();
      cluster_wait();
    } else if (warp == 9) {
      if (lane < 7) flag_wait(&g_cnt[lane], (ep + 1u) * 32u);
      cluster_wait();
      if (lane == 0) {
        TQ(3);
        asm volatile("fence.proxy.async;" ::: "memory");
        for (int k = 0; k < 7; k++) {
          mbar_expect(barA + 8 * k, 16384);
          tma3d_mc(sb + M_A + k * 16384 + rank * 8192, &tmA, barA + 8 * k, 0, 64 * k, 2 * mt + rank, (uint16_t)3);
          if (k == 0) TQ(4);
        }
      }
      __syncwarp();
#pragma unroll 1
      for (int p = 0; p < 2; p++) {
        named_bar(2 + p, 288);
        if (lane == 0) {
          TQ(7 + 2 * p);
          asm volatile("fence.acq_rel.gpu;" ::: "memory");
          TQ(8 + 2 * p);
          asm volatile("red.relaxed.gpu.global.add.u32 [%0], 1;" ::"l"(&g_cnt2[(mt * 2 + rank) * 2 + p]) : "memory");
        }
        __syncwarp();
      }
    } else if (warp == 10) {
      cluster_wait();
      if (lane == 0) {
#pragma unroll 1
        for (int p = 0; p < 2; p++) {
          flag_wait(&g_cnt2[(mt * 2 + rank) * 2 + p], (ep + 1u) * 4u);
          TQ(11 + p);
          mbar_arrive(barH + 8 * p);
        }
      }
    } else {
      if (lane < 7) flag_wait(&g_cnt[lane], (ep + 1u) * 32u);
      __syncwarp();
      float* cs = reinterpret_cast<float*>(smem + M_CS);
      for (int i = lane; i < 448; i += 32) cs[i] = __ldcg(&g_cs[(i >= 224 ? FF + i - 224 : i) + fj * 224]);
      __syncwarp();
      if (lane == 0) mbar_arrive(barS);
      cluster_wait();
    }
    __syncwarp();
    cluster_arrive(); cluster_wait();
  } else {
    asm volatile("setmaxnreg.inc.sync.aligned.u32 240;");
#define TPW 0
    const int wg = warp >> 2, wq = warp & 3;
    const bool elect = (tid & 127) == 0;
    const float* cs = reinterpret_cast<const float*>(smem + M_CS);
#define RELEASE(b) do { if (elect) mbar_arrive(b); } while (0)
#define PUBLISH(p) asm volatile("bar.arrive %0, 288;" ::"r"(2 + (p)) : "memory")
    const int dr = (lane & 7) + 8 * (lane >> 4), tc = 2 * wq + ((lane >> 3) & 1);
    const uint32_t aT = sb + M_A + wg * 8192 + dr * 128 + ((tc ^ (lane & 7)) << 4);
    uint4* hbase = reinterpret_cast<uint4*>(g_P) + (size_t)(mt * 8 * 8 + warp) * (14 * 32) + lane;
    float mb0, rs0, mb1, rs1;
    uint32_t pkA[64];
    {
      float accA[128];
      float s0 = 0.f, q0 = 0.f, s1 = 0.f, q1 = 0.f;
#pragma unroll
      for (int kb = 0; kb < 7; kb++) {
        const int s = kb % 3;
        mbar_wait(barA + 8 * kb, 0);
        uint32_t af[4][4];
#pragma unroll
        for (int k = 0; k < 4; k++) ldsm_x4_t(aT + kb * 16384 + k * 2048, af[k][0], af[k][1], af[k][2], af[k][3]);
        mbar_wait(barF + 8 * s, (kb / 3) & 1);
        TP(2, kb);
        const uint64_t db = mk_desc(sb + M_W + s * 32768, 8192, 1024, 1);
        wg_fence();
#pragma unroll
        for (int k = 0; k < 4; k++) wgmma_rs_n256(accA, af[k][0], af[k][1], af[k][2], af[k][3], db + k * 128, (kb | k) != 0);
        wg_commit();
        if (kb > 0) { wg_wait<1>(); RELEASE(barE + 8 * ((kb - 1) % 3)); }
#pragma unroll
        for (int k = 0; k < 4; k++) {
#pragma unroll
          for (int h = 0; h < 2; h++) {
            const float a = bflo(af[k][2 * h]), b = bfhi(af[k][2 * h]), c = bflo(af[k][2 * h + 1]), e = bfhi(af[k][2 * h + 1]);
            s0 += a + b; q0 = fmaf(a, a, fmaf(b, b, q0));
            s1 += c + e; q1 = fmaf(c, c, fmaf(e, e, q1));
          }
        }
      }
#pragma unroll
      for (int o = 1; o <= 2; o <<= 1) {
        s0 += __shfl_xor_sync(0xffffffffu, s0, o); q0 += __shfl_xor_sync(0xffffffffu, q0, o);
        s1 += __shfl_xor_sync(0xffffffffu, s1, o); q1 += __shfl_xor_sync(0xffffffffu, q1, o);
      }
      s0 *= (1.0f / DM); s1 *= (1.0f / DM);
      mb0 = bf16r(s0); mb1 = bf16r(s1);
      rs0 = __fdiv_rn(1.0f, bf16r(sqrtf(bf16r(bf16r(fmaxf(q0 * (1.0f / DM) - s0 * s0, 0.f)) + 1e-5f))));
      rs1 = __fdiv_rn(1.0f, bf16r(sqrtf(bf16r(bf16r(fmaxf(q1 * (1.0f / DM) - s1 * s1, 0.f)) + 1e-5f))));
      mbar_wait(barS, 0);
      wg_wait<0>();
      RELEASE(barE + 0);
      TP(2, 7);
      g1_pack<16, 128, 0>(accA, pkA, cs, mb0, rs0, mb1, rs1, lane);
      g1_pack<16, 128, 64>(accA, pkA + 32, cs + 224, mb0, rs0, mb1, rs1, lane);
    }
    uint32_t hf[56];
    uint32_t pkB[48];
    uint4* hown = hbase + (size_t)fj * (8 * 14 * 32);
    {
      float accG[48], accU[48];
#pragma unroll
      for (int kb = 0; kb < 7; kb++) {
        const int it = kb + 7, s = it % 3;
        uint32_t af[4][4];
#pragma unroll
        for (int k = 0; k < 4; k++) ldsm_x4_t(aT + kb * 16384 + k * 2048, af[k][0], af[k][1], af[k][2], af[k][3]);
        mbar_wait(barF + 8 * s, (it / 3) & 1);
        TP(2, 8 + kb);
        const uint64_t db = mk_desc(sb + M_W + s * 32768, 8192, 1024, 1);
        wg_fence();
#pragma unroll
        for (int k = 0; k < 4; k++) {
          wgmma_rs_n96(accG, af[k][0], af[k][1], af[k][2], af[k][3], db + k * 128, (kb | k) != 0);
          wgmma_rs_n96(accU, af[k][0], af[k][1], af[k][2], af[k][3], db + 1024 + k * 128, (kb | k) != 0);
        }
        wg_commit();
        if (kb > 0) { wg_wait<1>(); RELEASE(barE + 8 * ((it - 1) % 3)); }
        if (kb < 4) {
#pragma unroll
          for (int i = 0; i < 8; i++) hf[8 * kb + i] = glu2(pkA[8 * kb + i], pkA[32 + 8 * kb + i]);
          hown[(2 * kb) * 32] = make_uint4(hf[8 * kb], hf[8 * kb + 1], hf[8 * kb + 2], hf[8 * kb + 3]);
          hown[(2 * kb + 1) * 32] = make_uint4(hf[8 * kb + 4], hf[8 * kb + 5], hf[8 * kb + 6], hf[8 * kb + 7]);
          if (kb == 3) PUBLISH(0);
        }
      }
      wg_wait<0>();
      if (elect) { mbar_arrive(barE + 8 * (13 % 3)); mbar_arrive(barAf); }
      TP(2, 15);
      g1_pack<12, 48, 0>(accG, pkB, cs + 128, mb0, rs0, mb1, rs1, lane);
      g1_pack<12, 48, 0>(accU, pkB + 24, cs + 352, mb0, rs0, mb1, rs1, lane);
    }
    float acc[56];
    auto hsrc = [&](int i) -> const uint4* {
      int c, o;
      if (i < 38) { c = 1 + (i - 14) / 8; o = (i - 14) % 8; } else { c = 1 + (i - 38) / 6; o = 8 + (i - 38) % 6; }
      return hbase + (size_t)(4 * rank + ((fp + c) & 3)) * (8 * 14 * 32) + o * 32;
    };
    uint4 hq[5][4];
#pragma unroll
    for (int j = 0; j < 14; j++) {
      if (j == 1) mbar_wait(barH, 0);
      if (j == 6) mbar_wait(barH + 8, 0);
#pragma unroll
      for (int k = 0; k < 4; k++) {
        const int i = 4 * (j + 3) + k;
        if (j == 1 && k >= 2) hq[3][k] = __ldcg(hsrc(12 + k));
        if (j >= 1 && i < 56) hq[(j + 3) % 5][k] = __ldcg(hsrc(i));
      }
      mbar_wait(barW2 + 8 * j, 0);
      TP(3, j);
      const uint64_t db = mk_desc(sb + w2_slot(j, kp), 8192, 1024, 1);
      wg_fence();
#pragma unroll
      for (int k = 0; k < 4; k++) {
        const int i = 4 * j + k;
        if (i < 14) wgmma_rs_n112(acc, hf[4 * i], hf[4 * i + 1], hf[4 * i + 2], hf[4 * i + 3], db + k * 128, i != 0);
        else wgmma_rs_n112(acc, hq[j % 5][k].x, hq[j % 5][k].y, hq[j % 5][k].z, hq[j % 5][k].w, db + k * 128, 1);
      }
      wg_commit();
      if (j == 0) {
#pragma unroll
        for (int i = 0; i < 24; i++) hf[32 + i] = glu2(pkB[i], pkB[24 + i]);
#pragma unroll
        for (int q = 0; q < 6; q++) hown[(8 + q) * 32] = make_uint4(hf[32 + 4 * q], hf[33 + 4 * q], hf[34 + 4 * q], hf[35 + 4 * q]);
        PUBLISH(1);
      }
      if (j > 0) { wg_wait<1>(); if (j <= 4) RELEASE(barE2 + 8 * (j - 1)); }
    }
    wg_wait<0>();
    TP(3, 14);
    cluster_wait();
    if (wg != (int)rank) {
      asm volatile("bar.arrive 1, 256;" ::: "memory");
      const uint32_t xd = mapa(sb + M_XB, rank ^ 1) + (tid & 127) * 16;
#pragma unroll
      for (int q = 0; q < 7; q++)
        asm volatile("st.shared::cluster.v4.b32 [%0], {%1,%2,%3,%4};" ::"r"(xd + q * 2048), "r"(pack_bf16(acc[8 * q], acc[8 * q + 1])),
                     "r"(pack_bf16(acc[8 * q + 2], acc[8 * q + 3])), "r"(pack_bf16(acc[8 * q + 4], acc[8 * q + 5])),
                     "r"(pack_bf16(acc[8 * q + 6], acc[8 * q + 7])) : "memory");
      __syncwarp();
      if (lane == 0) asm volatile("mbarrier.arrive.release.cluster.shared::cluster.b64 _, [%0];" ::"r"(mapa(barX, rank ^ 1)) : "memory");
    } else {
      uint32_t hr[7][4];
      const int d0 = 112 * fp;
#pragma unroll
      for (int q = 0; q < 7; q++) {
        const int dd = d0 + 16 * q;
        ldsm_x4_t(aT + (dd >> 6) * 16384 + (dd & 63) * 128, hr[q][0], hr[q][1], hr[q][2], hr[q][3]);
      }
      { uint32_t ok; int it = 0;
        do { asm volatile("{.reg .pred p; mbarrier.try_wait.parity.acquire.cluster.shared::cta.b64 p, [%1], 0; selp.u32 %0,1,0,p;}"
                          : "=r"(ok) : "r"(barX) : "memory"); } while (!ok && ++it < (1 << 24)); }
      const uint32_t stg = sb + M_W + wq * 3840;
      const uint32_t so = stg + ((lane & 7) + 8 * ((lane >> 3) & 1)) * 240 + (lane >> 4) * 16;
      named_bar(1, 256);
#pragma unroll
      for (int q = 0; q < 7; q++) {
        const uint4 v = *reinterpret_cast<const uint4*>(smem + M_XB + q * 2048 + (tid & 127) * 16);
        const uint32_t m0 = pack_bf16(acc[8 * q] + bflo(v.x), acc[8 * q + 1] + bfhi(v.x)), m1 = pack_bf16(acc[8 * q + 2] + bflo(v.y), acc[8 * q + 3] + bfhi(v.y));
        const uint32_t m2 = pack_bf16(acc[8 * q + 4] + bflo(v.z), acc[8 * q + 5] + bfhi(v.z)), m3 = pack_bf16(acc[8 * q + 6] + bflo(v.w), acc[8 * q + 7] + bfhi(v.w));
        stsm_x4(so + q * 32, pack_bf16(bflo(hr[q][0]) + bflo(m0), bfhi(hr[q][0]) + bfhi(m0)), pack_bf16(bflo(hr[q][1]) + bflo(m1), bfhi(hr[q][1]) + bfhi(m1)),
                pack_bf16(bflo(hr[q][2]) + bflo(m2), bfhi(hr[q][2]) + bfhi(m2)), pack_bf16(bflo(hr[q][3]) + bflo(m3), bfhi(hr[q][3]) + bfhi(m3)));
      }
      __syncwarp();
      bf16* o = out + (size_t)(mt * 128 + 64 * wg + 16 * wq) * DM + d0;
#pragma unroll
      for (int k = 0; k < 7; k++) {
        const int c = lane + 32 * k;
        const int r = c / 14, ch = c - 14 * r;
        *reinterpret_cast<uint4*>(o + (size_t)r * DM + ch * 8) = *reinterpret_cast<const uint4*>(smem + M_W + wq * 3840 + r * 240 + ch * 16);
      }
    }
    TP(3, 15);
    if (tid == 0) {
      const unsigned int n = atomicAdd(&g_done, 1u);
      if ((n & 127u) == 127u) atomicAdd(&g_epoch, 1u);
    }
    __syncwarp();
    cluster_arrive(); cluster_wait();
#undef PUBLISH
#undef TPW
#undef RELEASE
  }
}

typedef CUresult (*EncFn)(CUtensorMap*, CUtensorMapDataType, cuuint32_t, void*, const cuuint64_t*, const cuuint64_t*,
                          const cuuint32_t*, const cuuint32_t*, CUtensorMapInterleave, CUtensorMapSwizzle,
                          CUtensorMapL2promotion, CUtensorMapFloatOOBfill);

static void make_map(EncFn enc, CUtensorMap* tm, const void* ptr, int rank, const uint64_t* dims, const uint64_t* strides_bytes,
                     const uint32_t* box, CUtensorMapSwizzle swz) {
  cuuint64_t gd[3], gs[2]; cuuint32_t bd[3], es[3] = {1, 1, 1};
  for (int i = 0; i < rank; i++) { gd[i] = dims[i]; bd[i] = box[i]; }
  for (int i = 0; i < rank - 1; i++) gs[i] = strides_bytes[i];
  enc(tm, CU_TENSOR_MAP_DATA_TYPE_BFLOAT16, rank, const_cast<void*>(ptr), gd, gs, bd, es, CU_TENSOR_MAP_INTERLEAVE_NONE, swz,
      CU_TENSOR_MAP_L2_PROMOTION_L2_128B, CU_TENSOR_MAP_FLOAT_OOB_FILL_NONE);
}

template <class K, class... Args>
static void launch_k(K kern, int grid, int block, int smem, bool pdl, Args... args) {
  cudaLaunchConfig_t cfg = {};
  cfg.gridDim = dim3(grid); cfg.blockDim = dim3(block); cfg.dynamicSmemBytes = smem; cfg.stream = cudaStreamPerThread;
  cudaLaunchAttribute at[1];
  at[0].id = cudaLaunchAttributeProgrammaticStreamSerialization;
  at[0].val.programmaticStreamSerializationAllowed = 1;
  cfg.attrs = at; cfg.numAttrs = pdl ? 1 : 0;
  cudaLaunchKernelEx(&cfg, kern, args...);
}

extern "C" void kernel_launch(void* const* d_in, const int* in_sizes, int n_in, void* d_out, int out_size) {
  const bf16* x   = (const bf16*)d_in[0];
  const bf16* Are = (const bf16*)d_in[1];
  const bf16* Aim = (const bf16*)d_in[2];
  const bf16* Bre = (const bf16*)d_in[3];
  const bf16* Bim = (const bf16*)d_in[4];
  const bf16* Cre = (const bf16*)d_in[5];
  const bf16* Cim = (const bf16*)d_in[6];
  const bf16* ldt = (const bf16*)d_in[7];
  const bf16* dsk = (const bf16*)d_in[8];
  const bf16* wg  = (const bf16*)d_in[10];
  const bf16* wu  = (const bf16*)d_in[11];
  const bf16* wd  = (const bf16*)d_in[12];

  static EncFn enc = nullptr;
  static void *p_hT = nullptr, *p_uT = nullptr, *p_xT = nullptr;
  if (!enc) {
    void* fn = nullptr; cudaDriverEntryPointQueryResult qr;
    cudaGetDriverEntryPoint("cuTensorMapEncodeTiled", &fn, cudaEnableDefault, &qr);
    enc = (EncFn)fn;
    cudaGetSymbolAddress(&p_hT, g_hT);
    cudaGetSymbolAddress(&p_uT, g_uT);
    cudaGetSymbolAddress(&p_xT, g_xT);
    cudaFuncSetAttribute(k_ssm, cudaFuncAttributeMaxDynamicSharedMemorySize, FRONT_SMEM);
    cudaFuncSetAttribute(k_mlp, cudaFuncAttributeMaxDynamicSharedMemorySize, M_TOTAL);
  }
  CUtensorMap tmA, tmG, tmU, tmD, tmLu, tmLx;
  {
    uint64_t dims[2] = {DM * 16, SEQ / 16}, st[1] = {DM * 32};
    uint32_t box[2] = {32, 128};
    make_map(enc, &tmLu, p_uT, 2, dims, st, box, CU_TENSOR_MAP_SWIZZLE_NONE);
    make_map(enc, &tmLx, p_xT, 2, dims, st, box, CU_TENSOR_MAP_SWIZZLE_NONE);
  }
  {
    uint64_t dims[3] = {64, DM, SEQ / 64}, st[2] = {SEQ * 2, 128};
    uint32_t box[3] = {64, 64, 1};
    make_map(enc, &tmA, p_hT, 3, dims, st, box, CU_TENSOR_MAP_SWIZZLE_128B);
  }
  {
    uint64_t dims[2] = {FF, DM}, st[1] = {FF * 2};
    uint32_t box[2] = {64, 64};
    make_map(enc, &tmG, wg, 2, dims, st, box, CU_TENSOR_MAP_SWIZZLE_128B);
    make_map(enc, &tmU, wu, 2, dims, st, box, CU_TENSOR_MAP_SWIZZLE_128B);
  }
  {
    uint64_t dims[2] = {DM, FF}, st[1] = {DM * 2};
    uint32_t box[2] = {64, 32};
    make_map(enc, &tmD, wd, 2, dims, st, box, CU_TENSOR_MAP_SWIZZLE_128B);
  }
  launch_k(k_ssm, 132, 512, FRONT_SMEM, false, Are, Aim, Bre, Bim, Cre, Cim, ldt, dsk, x, wg, wu, wd, tmLu, tmLx);
  launch_k(k_mlp, 128, 384, M_TOTAL, true, tmA, tmG, tmU, tmD, (bf16*)d_out);
}
```

```cpp
#include <cuda_runtime.h>
#include <cuda_bf16.h>
#include <cuda_fp16.h>
#include <cuda.h>
#include <stdint.h>

typedef __nv_bfloat16 bf16;

constexpr int SEQ = 2048;
constexpr int DM  = 448;
constexpr int NM  = 256;
constexpr int FF  = 1792;

__device__ __align__(1024) bf16  g_uT[DM * SEQ];
__device__ __align__(1024) bf16  g_xT[DM * SEQ];
__device__ __align__(1024) bf16  g_hT[DM * SEQ];
__device__ __align__(1024) bf16  g_P[SEQ * FF];
__device__ __align__(1024) bf16  g_dummy[16 * DM];
__device__ __align__(1024) float g_cs[2 * FF];

__device__ __forceinline__ uint32_t smem_u32(const void* p) { return (uint32_t)__cvta_generic_to_shared(p); }
__device__ __forceinline__ float bf16r(float v) { return __bfloat162float(__float2bfloat16_rn(v)); }
__device__ __forceinline__ float bflo(uint32_t w) { return __uint_as_float(w << 16); }
__device__ __forceinline__ float bfhi(uint32_t w) { return __uint_as_float(w & 0xffff0000u); }
__device__ __forceinline__ uint32_t pack_bf16(float lo, float hi) {
  uint32_t r; asm("cvt.rn.bf16x2.f32 %0, %1, %2;" : "=r"(r) : "f"(hi), "f"(lo)); return r;
}
__device__ __forceinline__ uint32_t pack_f16(float lo, float hi) {
  uint32_t r; asm("cvt.rn.f16x2.f32 %0, %1, %2;" : "=r"(r) : "f"(hi), "f"(lo)); return r;
}
__device__ __forceinline__ float ex2f(float x) { float r; asm("ex2.approx.ftz.f32 %0, %1;" : "=f"(r) : "f"(x)); return r; }
__device__ __forceinline__ void pdl_launch() { asm volatile("griddepcontrol.launch_dependents;"); }
__device__ __forceinline__ void pdl_wait() { asm volatile("griddepcontrol.wait;" ::: "memory"); }

__device__ __forceinline__ void mbar_init(uint32_t a, int c) { asm volatile("mbarrier.init.shared::cta.b64 [%0], %1;" ::"r"(a), "r"(c)); }
__device__ __forceinline__ void mbar_expect(uint32_t a, uint32_t bytes) {
  asm volatile("mbarrier.arrive.expect_tx.shared::cta.b64 _, [%0], %1;" ::"r"(a), "r"(bytes) : "memory");
}
__device__ __forceinline__ void mbar_arrive(uint32_t a) { asm volatile("mbarrier.arrive.shared::cta.b64 _, [%0];" ::"r"(a) : "memory"); }
__device__ __forceinline__ void mbar_arrive_cluster(uint32_t remote_a) {
  asm volatile("mbarrier.arrive.shared::cluster.b64 _, [%0];" ::"r"(remote_a) : "memory");
}
__device__ __forceinline__ void mbar_wait(uint32_t a, uint32_t ph) {
  uint32_t ok; int it = 0;
  do {
    asm volatile("{.reg .pred p; mbarrier.try_wait.parity.shared::cta.b64 p, [%1], %2; selp.u32 %0,1,0,p;}"
                 : "=r"(ok) : "r"(a), "r"(ph) : "memory");
  } while (!ok && ++it < (1 << 24));
}
__device__ __forceinline__ void flag_wait(const unsigned int* p, unsigned int target) {
  unsigned int v; int it = 0;
  asm volatile("ld.acquire.gpu.global.u32 %0, [%1];" : "=r"(v) : "l"(p) : "memory");
  if ((int)(v - target) >= 0) return;
  while (true) {
    __nanosleep(32);
    asm volatile("ld.relaxed.gpu.global.u32 %0, [%1];" : "=r"(v) : "l"(p) : "memory");
    if ((int)(v - target) >= 0 || ++it > (1 << 22)) break;
  }
  asm volatile("ld.acquire.gpu.global.u32 %0, [%1];" : "=r"(v) : "l"(p) : "memory");
}
__device__ __forceinline__ uint4 ld_relaxed_v4(const uint4* p) {
  uint4 v; asm volatile("ld.relaxed.gpu.global.v4.u32 {%0,%1,%2,%3}, [%4];" : "=r"(v.x), "=r"(v.y), "=r"(v.z), "=r"(v.w) : "l"(p) : "memory"); return v;
}
__device__ __forceinline__ void st_relaxed_v4(uint4* p, uint32_t a, uint32_t b, uint32_t c, uint32_t d) {
  asm volatile("st.relaxed.gpu.global.v4.u32 [%0], {%1,%2,%3,%4};" ::"l"(p), "r"(a), "r"(b), "r"(c), "r"(d) : "memory");
}
__device__ __forceinline__ uint32_t mapa(uint32_t a, uint32_t rank) {
  uint32_t r; asm volatile("mapa.shared::cluster.u32 %0, %1, %2;" : "=r"(r) : "r"(a), "r"(rank)); return r;
}
__device__ __forceinline__ void cluster_arrive() { asm volatile("barrier.cluster.arrive.release.aligned;" ::: "memory"); }
__device__ __forceinline__ void cluster_wait() { asm volatile("barrier.cluster.wait.acquire.aligned;" ::: "memory"); }
__device__ __forceinline__ void fence_async() { asm volatile("fence.proxy.async.shared::cta;" ::: "memory"); }
__device__ __forceinline__ void named_bar(int id, int n) { asm volatile("bar.sync %0, %1;" ::"r"(id), "r"(n) : "memory"); }

__device__ __forceinline__ void tma2d(uint32_t dst, const CUtensorMap* tm, uint32_t bar, int c0, int c1) {
  asm volatile("cp.async.bulk.tensor.2d.shared::cluster.global.mbarrier::complete_tx::bytes [%0], [%1, {%3,%4}], [%2];"
               ::"r"(dst), "l"(tm), "r"(bar), "r"(c0), "r"(c1) : "memory");
}
__device__ __forceinline__ void tma3d(uint32_t dst, const CUtensorMap* tm, uint32_t bar, int c0, int c1, int c2) {
  asm volatile("cp.async.bulk.tensor.3d.shared::cluster.global.mbarrier::complete_tx::bytes [%0], [%1, {%3,%4,%5}], [%2];"
               ::"r"(dst), "l"(tm), "r"(bar), "r"(c0), "r"(c1), "r"(c2) : "memory");
}
__device__ __forceinline__ void tma3d_mc(uint32_t dst, const CUtensorMap* tm, uint32_t bar, int c0, int c1, int c2, uint16_t mask) {
  asm volatile("cp.async.bulk.tensor.3d.shared::cluster.global.mbarrier::complete_tx::bytes.multicast::cluster [%0], [%1, {%3,%4,%5}], [%2], %6;"
               ::"r"(dst), "l"(tm), "r"(bar), "r"(c0), "r"(c1), "r"(c2), "h"(mask) : "memory");
}
__device__ __forceinline__ void tma2d_store(const CUtensorMap* tm, uint32_t src, int c0, int c1) {
  asm volatile("cp.async.bulk.tensor.2d.global.shared::cta.bulk_group [%0, {%2,%3}], [%1];"
               ::"l"(tm), "r"(src), "r"(c0), "r"(c1) : "memory");
}
__device__ __forceinline__ void bulk_commit() { asm volatile("cp.async.bulk.commit_group;" ::: "memory"); }
template <int N> __device__ __forceinline__ void bulk_wait_read() { asm volatile("cp.async.bulk.wait_group.read %0;" ::"n"(N) : "memory"); }
template <int N> __device__ __forceinline__ void bulk_wait() { asm volatile("cp.async.bulk.wait_group %0;" ::"n"(N) : "memory"); }
__device__ __forceinline__ void prefetch_tm(const CUtensorMap* tm) { asm volatile("prefetch.tensormap [%0];" ::"l"(tm) : "memory"); }

__device__ __forceinline__ void wg_fence() { asm volatile("wgmma.fence.sync.aligned;" ::: "memory"); }
__device__ __forceinline__ void wg_commit() { asm volatile("wgmma.commit_group.sync.aligned;" ::: "memory"); }
template <int N> __device__ __forceinline__ void wg_wait() { asm volatile("wgmma.wait_group.sync.aligned %0;" ::"n"(N) : "memory"); }
__device__ __forceinline__ uint64_t mk_desc(uint32_t addr, uint32_t lbo, uint32_t sbo, uint32_t swz) {
  return (uint64_t)((addr & 0x3FFFF) >> 4) | ((uint64_t)(lbo >> 4) << 16) | ((uint64_t)(sbo >> 4) << 32) | ((uint64_t)swz << 62);
}
__device__ __forceinline__ void ldsm_x4(uint32_t a, uint32_t& r0, uint32_t& r1, uint32_t& r2, uint32_t& r3) {
  asm volatile("ldmatrix.sync.aligned.m8n8.x4.shared.b16 {%0,%1,%2,%3}, [%4];" : "=r"(r0), "=r"(r1), "=r"(r2), "=r"(r3) : "r"(a));
}
__device__ __forceinline__ void ldsm_x4_t(uint32_t a, uint32_t& r0, uint32_t& r1, uint32_t& r2, uint32_t& r3) {
  asm volatile("ldmatrix.sync.aligned.m8n8.x4.trans.shared.b16 {%0,%1,%2,%3}, [%4];" : "=r"(r0), "=r"(r1), "=r"(r2), "=r"(r3) : "r"(a));
}
__device__ __forceinline__ void ldsm_x2_t(uint32_t a, uint32_t& r0, uint32_t& r1) {
  asm volatile("ldmatrix.sync.aligned.m8n8.x2.trans.shared.b16 {%0,%1}, [%2];" : "=r"(r0), "=r"(r1) : "r"(a));
}
__device__ __forceinline__ void stsm_x4(uint32_t a, uint32_t r0, uint32_t r1, uint32_t r2, uint32_t r3) {
  asm volatile("stmatrix.sync.aligned.m8n8.x4.shared.b16 [%0], {%1,%2,%3,%4};" ::"r"(a), "r"(r0), "r"(r1), "r"(r2), "r"(r3) : "memory");
}
__device__ __forceinline__ void stsm_x2(uint32_t a, uint32_t r0, uint32_t r1) {
  asm volatile("stmatrix.sync.aligned.m8n8.x2.shared.b16 [%0], {%1,%2};" ::"r"(a), "r"(r0), "r"(r1) : "memory");
}
__device__ __forceinline__ uint32_t lds32(uint32_t a) { uint32_t r; asm volatile("ld.shared.u32 %0, [%1];" : "=r"(r) : "r"(a)); return r; }
__device__ __forceinline__ void mma_bf16(float (&c)[4], uint32_t a0, uint32_t a1, uint32_t a2, uint32_t a3, uint32_t b0, uint32_t b1) {
  asm volatile("mma.sync.aligned.m16n8k16.row.col.f32.bf16.bf16.f32 {%0,%1,%2,%3}, {%4,%5,%6,%7}, {%8,%9}, {%0,%1,%2,%3};"
               : "+f"(c[0]), "+f"(c[1]), "+f"(c[2]), "+f"(c[3]) : "r"(a0), "r"(a1), "r"(a2), "r"(a3), "r"(b0), "r"(b1));
}
__device__ __forceinline__ void mma_f16(float (&c)[4], uint32_t a0, uint32_t a1, uint32_t a2, uint32_t a3, uint32_t b0, uint32_t b1) {
  asm volatile("mma.sync.aligned.m16n8k16.row.col.f32.f16.f16.f32 {%0,%1,%2,%3}, {%4,%5,%6,%7}, {%8,%9}, {%0,%1,%2,%3};"
               : "+f"(c[0]), "+f"(c[1]), "+f"(c[2]), "+f"(c[3]) : "r"(a0), "r"(a1), "r"(a2), "r"(a3), "r"(b0), "r"(b1));
}
__device__ __forceinline__ void cp_async16(uint32_t dst, const void* src) {
  asm volatile("cp.async.cg.shared.global [%0], [%1], 16;" ::"r"(dst), "l"(src) : "memory");
}
__device__ __forceinline__ void cp_async_wait_all() { asm volatile("cp.async.wait_all;" ::: "memory"); }

__device__ unsigned int g_epoch;
__device__ unsigned int g_cnt[16];
__device__ unsigned int g_cnt2[256];
__device__ unsigned int g_done;

constexpr int LN_PITCH = 912;
constexpr int LN_STAT  = 16 * LN_PITCH;
constexpr int LN_SMEM  = LN_STAT + 7 * 128;
__device__ __forceinline__ void ln1_load(const bf16* __restrict__ x, int tile, unsigned char* sm) {
  const int r = (threadIdx.x >> 4) & 15, c = threadIdx.x & 15;
  const uint32_t dst = smem_u32(sm) + r * LN_PITCH + c * 16;
  const bf16* src = x + (size_t)(tile * 16 + r) * DM + c * 8;
#pragma unroll
  for (int k = 0; k < 4; k++)
    if (k < 3 || c < 8) cp_async16(dst + k * 256, src + k * 128);
}
__device__ __forceinline__ void ln1_tile(int tile, unsigned char* sm) {
  const uint32_t sb = smem_u32(sm);
  const int lane = threadIdx.x & 31, w = (threadIdx.x >> 5) - 8;
  const int g = lane >> 2, t = lane & 3;
  cp_async_wait_all();
  named_bar(14, 256);
  if (w < 7) {
    float s1[4] = {0.f, 0.f, 0.f, 0.f}, qa[4] = {0.f, 0.f, 0.f, 0.f}, qb[4] = {0.f, 0.f, 0.f, 0.f};
    const uint32_t ad = sb + ((lane & 7) + 8 * ((lane >> 3) & 1)) * LN_PITCH + (lane >> 4) * 16 + w * 128;
#pragma unroll
    for (int k = 0; k < 4; k++) {
      uint32_t a0, a1, a2, a3;
      ldsm_x4(ad + k * 32, a0, a1, a2, a3);
      mma_bf16(s1, a0, a1, a2, a3, 0x3f803f80u, 0x3f803f80u);
      mma_bf16(qa, a0, a1, a2, a3, a0, a2);
      mma_bf16(qb, a0, a1, a2, a3, a1, a3);
    }
    if (t == (g >> 1)) {
      float2* st = reinterpret_cast<float2*>(sm + LN_STAT) + w * 16;
      st[g]     = make_float2(s1[0], (g & 1) ? qa[1] : qa[0]);
      st[g + 8] = make_float2(s1[2], (g & 1) ? qb[3] : qb[2]);
    }
  }
  named_bar(14, 256);
  if (w < 7) {
    float mb[4], rd[4];
    {
      const float2* st = reinterpret_cast<const float2*>(sm + LN_STAT) + (lane & 15);
      float sx = 0.f, sy = 0.f;
#pragma unroll
      for (int i = 0; i < 7; i++) { const float2 p = st[16 * i]; sx += p.x; sy += p.y; }
      const float mean = sx * (1.0f / DM);
      const float var = fmaxf(sy * (1.0f / DM) - mean * mean, 0.f);
      const float m = bf16r(mean);
      const float r = __fdiv_rn(1.0f, bf16r(sqrtf(bf16r(bf16r(var) + 1e-5f))));
#pragma unroll
      for (int e = 0; e < 4; e++) {
        mb[e] = __shfl_sync(0xffffffffu, m, 4 * t + e);
        rd[e] = __shfl_sync(0xffffffffu, r, 4 * t + e);
      }
    }
    const int r8 = lane & 7;
    const int tok = 4 * (r8 >> 1) + (r8 & 1) + 2 * ((lane >> 3) & 1);
    const uint32_t ad = sb + tok * LN_PITCH + (w * 64 + (lane >> 4) * 8) * 2;
    const size_t go = (size_t)(tile * DM + w * 64 + g) * 16 + 4 * t;
#pragma unroll
    for (int k = 0; k < 4; k++) {
      uint32_t v[4];
      ldsm_x4_t(ad + k * 32, v[0], v[1], v[2], v[3]);
#pragma unroll
      for (int h = 0; h < 2; h++) {
        const uint32_t d0 = pack_bf16(bflo(v[2 * h]) - mb[0], bfhi(v[2 * h]) - mb[1]);
        const uint32_t d1 = pack_bf16(bflo(v[2 * h + 1]) - mb[2], bfhi(v[2 * h + 1]) - mb[3]);
        const size_t o = go + (size_t)(16 * k + 8 * h) * 16;
        *reinterpret_cast<uint2*>(g_uT + o) = make_uint2(pack_bf16(bflo(d0) * rd[0], bfhi(d0) * rd[1]), pack_bf16(bflo(d1) * rd[2], bfhi(d1) * rd[3]));
        *reinterpret_cast<uint2*>(g_xT + o) = make_uint2(v[2 * h], v[2 * h + 1]);
      }
    }
    asm volatile("bar.arrive 12, 256;" ::: "memory");
  } else {
    named_bar(12, 256);
    if (lane == 0) {
      __threadfence();
      asm volatile("red.relaxed.gpu.global.add.u32 [%0], 1;" ::"l"(&g_cnt[7]) : "memory");
    }
    __syncwarp();
  }
}

constexpr int CS_SMEM = 448 * 64 + 16 * 128;
__device__ __forceinline__ void colsum_load(const bf16* __restrict__ wg, const bf16* __restrict__ wu, int b2, unsigned char* sm) {
  const bf16* W = (b2 >= 56 ? wu : wg) + (b2 % 56) * 32;
  const uint32_t sb = smem_u32(sm);
#pragma unroll
  for (int k = 0; k < 7; k++)
    cp_async16(sb + (threadIdx.x & 255) * 16 + k * 4096, W + (size_t)((threadIdx.x & 255) >> 2) * FF + (threadIdx.x & 3) * 8 + (size_t)k * 64 * FF);
}
__device__ __forceinline__ void colsum_reduce(unsigned char* sm) {
  const int lane = threadIdx.x & 31, w = (threadIdx.x >> 5) & 7;
  if (w >= 7) return;
  float acc[4][4];
#pragma unroll
  for (int i = 0; i < 4; i++) { acc[i][0] = acc[i][1] = acc[i][2] = acc[i][3] = 0.f; }
  const uint32_t ad = smem_u32(sm) + (w * 64 + (lane & 15)) * 64 + (lane >> 4) * 16;
#pragma unroll
  for (int k = 0; k < 4; k++) {
#pragma unroll
    for (int h = 0; h < 2; h++) {
      uint32_t b0, b1, b2, b3;
      ldsm_x4_t(ad + k * 1024 + h * 32, b0, b1, b2, b3);
      mma_bf16(acc[2 * h], 0x3f803f80u, 0x3f803f80u, 0x3f803f80u, 0x3f803f80u, b0, b1);
      mma_bf16(acc[2 * h + 1], 0x3f803f80u, 0x3f803f80u, 0x3f803f80u, 0x3f803f80u, b2, b3);
    }
  }
  if (lane < 4) {
    float* sf = reinterpret_cast<float*>(sm + 448 * 64) + w * 32 + 2 * lane;
#pragma unroll
    for (int i = 0; i < 4; i++) *reinterpret_cast<float2*>(sf + 8 * i) = make_float2(acc[i][0], acc[i][1]);
  }
}
__device__ __forceinline__ void colsum_store(int b2, unsigned char* sm) {
  const float* sf = reinterpret_cast<const float*>(sm + 448 * 64);
  const int lane = threadIdx.x & 31;
  float s = 0.f;
#pragma unroll
  for (int i = 0; i < 7; i++) s += sf[i * 32 + lane];
  g_cs[(b2 >= 56 ? FF : 0) + (b2 % 56) * 32 + lane] = s;
}
__device__ __forceinline__ void wgmma_rs_n96(float (&d)[48], uint32_t a0, uint32_t a1, uint32_t a2, uint32_t a3, uint64_t db, int sc) {
  asm volatile("{\n.reg .pred p;\nsetp.ne.b32 p, %53, 0;\n"
    "wgmma.mma_async.sync.aligned.m64n96k16.f32.bf16.bf16 {%0, %1, %2, %3, %4, %5, %6, %7, %8, %9, %10, %11, %12, %13, %14, %15, %16, %17, %18, %19, %20, %21, %22, %23, %24, %25, %26, %27, %28, %29, %30, %31, %32, %33, %34, %35, %36, %37, %38, %39, %40, %41, %42, %43, %44, %45, %46, %47}, {%48, %49, %50, %51}, %52, p, 1, 1, 1;\n}\n"
    : "+f"(d[0]), "+f"(d[1]), "+f"(d[2]), "+f"(d[3]), "+f"(d[4]), "+f"(d[5]), "+f"(d[6]), "+f"(d[7]), "+f"(d[8]), "+f"(d[9]), "+f"(d[10]), "+f"(d[11]), "+f"(d[12]), "+f"(d[13]), "+f"(d[14]), "+f"(d[15]), "+f"(d[16]), "+f"(d[17]), "+f"(d[18]), "+f"(d[19]), "+f"(d[20]), "+f"(d[21]), "+f"(d[22]), "+f"(d[23]), "+f"(d[24]), "+f"(d[25]), "+f"(d[26]), "+f"(d[27]), "+f"(d[28]), "+f"(d[29]), "+f"(d[30]), "+f"(d[31]), "+f"(d[32]), "+f"(d[33]), "+f"(d[34]), "+f"(d[35]), "+f"(d[36]), "+f"(d[37]), "+f"(d[38]), "+f"(d[39]), "+f"(d[40]), "+f"(d[41]), "+f"(d[42]), "+f"(d[43]), "+f"(d[44]), "+f"(d[45]), "+f"(d[46]), "+f"(d[47])
    : "r"(a0), "r"(a1), "r"(a2), "r"(a3), "l"(db), "r"(sc));
}
__device__ __forceinline__ void wgmma_rs_n256(float (&d)[128], uint32_t a0, uint32_t a1, uint32_t a2, uint32_t a3, uint64_t db, int sc) {
  asm volatile("{\n.reg .pred p;\nsetp.ne.b32 p, %133, 0;\n"
    "wgmma.mma_async.sync.aligned.m64n256k16.f32.bf16.bf16 {%0, %1, %2, %3, %4, %5, %6, %7, %8, %9, %10, %11, %12, %13, %14, %15, %16, %17, %18, %19, %20, %21, %22, %23, %24, %25, %26, %27, %28, %29, %30, %31, %32, %33, %34, %35, %36, %37, %38, %39, %40, %41, %42, %43, %44, %45, %46, %47, %48, %49, %50, %51, %52, %53, %54, %55, %56, %57, %58, %59, %60, %61, %62, %63, %64, %65, %66, %67, %68, %69, %70, %71, %72, %73, %74, %75, %76, %77, %78, %79, %80, %81, %82, %83, %84, %85, %86, %87, %88, %89, %90, %91, %92, %93, %94, %95, %96, %97, %98, %99, %100, %101, %102, %103, %104, %105, %106, %107, %108, %109, %110, %111, %112, %113, %114, %115, %116, %117, %118, %119, %120, %121, %122, %123, %124, %125, %126, %127}, {%128, %129, %130, %131}, %132, p, 1, 1, 1;\n}\n"
    : "+f"(d[0]), "+f"(d[1]), "+f"(d[2]), "+f"(d[3]), "+f"(d[4]), "+f"(d[5]), "+f"(d[6]), "+f"(d[7]), "+f"(d[8]), "+f"(d[9]), "+f"(d[10]), "+f"(d[11]), "+f"(d[12]), "+f"(d[13]), "+f"(d[14]), "+f"(d[15]), "+f"(d[16]), "+f"(d[17]), "+f"(d[18]), "+f"(d[19]), "+f"(d[20]), "+f"(d[21]), "+f"(d[22]), "+f"(d[23]), "+f"(d[24]), "+f"(d[25]), "+f"(d[26]), "+f"(d[27]), "+f"(d[28]), "+f"(d[29]), "+f"(d[30]), "+f"(d[31]), "+f"(d[32]), "+f"(d[33]), "+f"(d[34]), "+f"(d[35]), "+f"(d[36]), "+f"(d[37]), "+f"(d[38]), "+f"(d[39]), "+f"(d[40]), "+f"(d[41]), "+f"(d[42]), "+f"(d[43]), "+f"(d[44]), "+f"(d[45]), "+f"(d[46]), "+f"(d[47]), "+f"(d[48]), "+f"(d[49]), "+f"(d[50]), "+f"(d[51]), "+f"(d[52]), "+f"(d[53]), "+f"(d[54]), "+f"(d[55]), "+f"(d[56]), "+f"(d[57]), "+f"(d[58]), "+f"(d[59]), "+f"(d[60]), "+f"(d[61]), "+f"(d[62]), "+f"(d[63]), "+f"(d[64]), "+f"(d[65]), "+f"(d[66]), "+f"(d[67]), "+f"(d[68]), "+f"(d[69]), "+f"(d[70]), "+f"(d[71]), "+f"(d[72]), "+f"(d[73]), "+f"(d[74]), "+f"(d[75]), "+f"(d[76]), "+f"(d[77]), "+f"(d[78]), "+f"(d[79]), "+f"(d[80]), "+f"(d[81]), "+f"(d[82]), "+f"(d[83]), "+f"(d[84]), "+f"(d[85]), "+f"(d[86]), "+f"(d[87]), "+f"(d[88]), "+f"(d[89]), "+f"(d[90]), "+f"(d[91]), "+f"(d[92]), "+f"(d[93]), "+f"(d[94]), "+f"(d[95]), "+f"(d[96]), "+f"(d[97]), "+f"(d[98]), "+f"(d[99]), "+f"(d[100]), "+f"(d[101]), "+f"(d[102]), "+f"(d[103]), "+f"(d[104]), "+f"(d[105]), "+f"(d[106]), "+f"(d[107]), "+f"(d[108]), "+f"(d[109]), "+f"(d[110]), "+f"(d[111]), "+f"(d[112]), "+f"(d[113]), "+f"(d[114]), "+f"(d[115]), "+f"(d[116]), "+f"(d[117]), "+f"(d[118]), "+f"(d[119]), "+f"(d[120]), "+f"(d[121]), "+f"(d[122]), "+f"(d[123]), "+f"(d[124]), "+f"(d[125]), "+f"(d[126]), "+f"(d[127])
    : "r"(a0), "r"(a1), "r"(a2), "r"(a3), "l"(db), "r"(sc));
}
__device__ __forceinline__ void wgmma_rs_n112(float (&d)[56], uint32_t a0, uint32_t a1, uint32_t a2, uint32_t a3, uint64_t db, int sc) {
  asm volatile("{\n.reg .pred p;\nsetp.ne.b32 p, %61, 0;\n"
    "wgmma.mma_async.sync.aligned.m64n112k16.f32.bf16.bf16 {%0, %1, %2, %3, %4, %5, %6, %7, %8, %9, %10, %11, %12, %13, %14, %15, %16, %17, %18, %19, %20, %21, %22, %23, %24, %25, %26, %27, %28, %29, %30, %31, %32, %33, %34, %35, %36, %37, %38, %39, %40, %41, %42, %43, %44, %45, %46, %47, %48, %49, %50, %51, %52, %53, %54, %55}, {%56, %57, %58, %59}, %60, p, 1, 1, 1;\n}\n"
    : "+f"(d[0]), "+f"(d[1]), "+f"(d[2]), "+f"(d[3]), "+f"(d[4]), "+f"(d[5]), "+f"(d[6]), "+f"(d[7]), "+f"(d[8]), "+f"(d[9]), "+f"(d[10]), "+f"(d[11]), "+f"(d[12]), "+f"(d[13]), "+f"(d[14]), "+f"(d[15]), "+f"(d[16]), "+f"(d[17]), "+f"(d[18]), "+f"(d[19]), "+f"(d[20]), "+f"(d[21]), "+f"(d[22]), "+f"(d[23]), "+f"(d[24]), "+f"(d[25]), "+f"(d[26]), "+f"(d[27]), "+f"(d[28]), "+f"(d[29]), "+f"(d[30]), "+f"(d[31]), "+f"(d[32]), "+f"(d[33]), "+f"(d[34]), "+f"(d[35]), "+f"(d[36]), "+f"(d[37]), "+f"(d[38]), "+f"(d[39]), "+f"(d[40]), "+f"(d[41]), "+f"(d[42]), "+f"(d[43]), "+f"(d[44]), "+f"(d[45]), "+f"(d[46]), "+f"(d[47]), "+f"(d[48]), "+f"(d[49]), "+f"(d[50]), "+f"(d[51]), "+f"(d[52]), "+f"(d[53]), "+f"(d[54]), "+f"(d[55])
    : "r"(a0), "r"(a1), "r"(a2), "r"(a3), "l"(db), "r"(sc));
}

struct cplx { float re, im; };
__device__ __forceinline__ cplx cmul(cplx a, cplx b) {
  cplx r; r.re = a.re * b.re - a.im * b.im; r.im = a.re * b.im + a.im * b.re; return r;
}
__device__ __forceinline__ cplx zpow_acc(float a2, float bt, float c) {
  float mag = ex2f(a2 * c);
  float tr = bt * c;
  tr -= rintf(tr);
  float ang = tr * 6.283185307179586f;
  cplx r; r.re = mag * __cosf(ang); r.im = mag * __sinf(ang); return r;
}

constexpr int SB_TAB  = 0;
constexpr int SB_WREG = 7168;
constexpr int UZ = 40;
constexpr int SB_U    = 4 * SB_WREG;
constexpr int SB_KV   = SB_U + 172 * 36;
constexpr int SB_TOTAL = (SB_KV + 644 * 4 + 127) / 128 * 128;
constexpr int SB_F3   = 0;
constexpr int SB_F2   = 1792;
constexpr int SB_Y    = 4096;
constexpr int SB_KD   = SB_Y;
constexpr int SB_KDO  = SB_KD + 2240;
constexpr int FR_LN = 4 * SB_TOTAL;
constexpr int FR_CS = (FR_LN + LN_SMEM + 127) / 128 * 128;
constexpr int FR_X = FR_CS + CS_SMEM;
constexpr int FR_BAR = FR_X + 16384;
constexpr int FRONT_SMEM = FR_BAR + 16;

__device__ __forceinline__ int rowaddr(int r) { return 32 * r + 16 * (r >> 2); }
struct hc { __half2 re, im; };
__device__ __forceinline__ hc bcast(cplx a) { hc r; r.re = __float2half2_rn(a.re); r.im = __float2half2_rn(a.im); return r; }
__device__ __forceinline__ hc hmul(hc v, hc s) {
  hc r;
  r.re = __hfma2(v.re, s.re, __hneg2(__hmul2(v.im, s.im)));
  r.im = __hfma2(v.re, s.im, __hmul2(v.im, s.re));
  return r;
}
__device__ __forceinline__ uint32_t h2u(__half2 h) { return *reinterpret_cast<uint32_t*>(&h); }
__device__ __forceinline__ void gen8(unsigned char* p, cplx s, cplx r1, hc r1sq, hc r2) {
  const cplx v1 = cmul(s, r1);
  hc p0; p0.re = __floats2half2_rn(s.re, v1.re); p0.im = __floats2half2_rn(s.im, v1.im);
  const hc p1 = hmul(p0, r1sq), p2 = hmul(p0, r2), p3 = hmul(p1, r2);
  *reinterpret_cast<uint4*>(p) = make_uint4(h2u(p0.re), h2u(p1.re), h2u(p2.re), h2u(p3.re));
  *reinterpret_cast<uint4*>(p + 8 * 112) = make_uint4(h2u(p0.im), h2u(p1.im), h2u(p2.im), h2u(p3.im));
}
__device__ __forceinline__ cplx csq(cplx a) { cplx r; r.re = a.re * a.re - a.im * a.im; r.im = 2.f * a.re * a.im; return r; }
__device__ __forceinline__ cplx cconj(cplx a) { a.im = -a.im; return a; }
__device__ __forceinline__ uint2 lds64(uint32_t a) { uint2 r; asm volatile("ld.shared.v2.u32 {%0,%1}, [%2];" : "=r"(r.x), "=r"(r.y) : "r"(a)); return r; }

__global__ void __launch_bounds__(512, 1) k_ssm(const bf16* __restrict__ Are, const bf16* __restrict__ Aim,
                                             const bf16* __restrict__ Bre, const bf16* __restrict__ Bim,
                                             const bf16* __restrict__ Cre, const bf16* __restrict__ Cim,
                                             const bf16* __restrict__ log_dt, const bf16* __restrict__ Dskip,
                                             const bf16* __restrict__ x, const bf16* __restrict__ wg,
                                             const bf16* __restrict__ wu, const bf16* __restrict__ wd,
                                             const __grid_constant__ CUtensorMap tmU, const __grid_constant__ CUtensorMap tmX) {
  pdl_launch();
  extern __shared__ __align__(1024) unsigned char smem_all[];
  const int sub = threadIdx.x >> 7;
  const int tid = threadIdx.x & 127, lane = tid & 31;
  const int bar = 1 + sub;
  unsigned char* sm = smem_all + sub * SB_TOTAL;
  const uint32_t sbase = smem_u32(sm);
  const int w = ((tid >> 5) + sub) & 3;
  const int g = lane >> 2, t = lane & 3;
  const bool upper = threadIdx.x >= 256;
  const int hbar = upper ? 14 : 13;
  const bool do_ln = upper && blockIdx.x < 128;
  if (do_ln) ln1_load(x, blockIdx.x, smem_all + FR_LN);
  if (blockIdx.x >= 112) {
    if (do_ln) ln1_tile(blockIdx.x, smem_all + FR_LN);
    if (upper) named_bar(hbar, 256);
    const int t0 = (blockIdx.x - 112) + (upper ? 20 : 0);
    unsigned char* cs = smem_all + (upper ? 3 * CS_SMEM : 0);
#pragma unroll
    for (int i = 0; i < 3; i++)
      if (t0 + 40 * i < 112) colsum_load(wg, wu, t0 + 40 * i, cs + i * CS_SMEM);
    for (int i = (blockIdx.x - 112) * 512 + threadIdx.x; i < FF * DM * 2 / 128; i += 20 * 512)
      asm volatile("prefetch.global.L2 [%0];" ::"l"(reinterpret_cast<const char*>(wd) + (size_t)i * 128));
    cp_async_wait_all();
    named_bar(hbar, 256);
#pragma unroll
    for (int i = 0; i < 3; i++)
      if (t0 + 40 * i < 112) colsum_reduce(cs + i * CS_SMEM);
    named_bar(hbar, 256);
    const int wi = (threadIdx.x >> 5) & 7;
    if (wi < 3 && t0 + 40 * wi < 112) colsum_store(t0 + 40 * wi, cs + wi * CS_SMEM);
    named_bar(hbar, 256);
    if ((threadIdx.x & 255) == 0) {
      __threadfence();
      asm volatile("red.relaxed.gpu.global.add.u32 [%0], 1;" ::"l"(&g_cnt[8]) : "memory");
    }
    return;
  }
  const int d = blockIdx.x * 4 + sub;
  const int pidx = (d * NM + 64 * w) / 2 + lane;
  const uint32_t pAre = __ldg(reinterpret_cast<const uint32_t*>(Are) + pidx), pAim = __ldg(reinterpret_cast<const uint32_t*>(Aim) + pidx);
  const uint32_t pBre = __ldg(reinterpret_cast<const uint32_t*>(Bre) + pidx), pBim = __ldg(reinterpret_cast<const uint32_t*>(Bim) + pidx);
  const uint32_t pCre = __ldg(reinterpret_cast<const uint32_t*>(Cre) + pidx), pCim = __ldg(reinterpret_cast<const uint32_t*>(Cim) + pidx);
  const float dt = bf16r(expf(__bfloat162float(log_dt[d])));
  const uint32_t dsk2 = (uint32_t)__bfloat16_as_ushort(Dskip[d]) * 0x10001u;
  if (upper) ln1_tile(blockIdx.x, smem_all + FR_LN);
  if (tid < 90) *reinterpret_cast<uint4*>(sm + SB_U + tid * 16) = make_uint4(0, 0, 0, 0);
  if (tid >= 96 && tid < 105) *reinterpret_cast<uint4*>(sm + SB_U + 168 * 36 + (tid - 96) * 16) = make_uint4(0, 0, 0, 0);
  float w0re, w0im, w1re, w1im;
  {
    const float br0 = dt * bflo(pBre), bi0 = dt * bflo(pBim), br1 = dt * bfhi(pBre), bi1 = dt * bfhi(pBim);
    w0re = bflo(pCre) * br0 - bflo(pCim) * bi0; w0im = bflo(pCre) * bi0 + bflo(pCim) * br0;
    w1re = bfhi(pCre) * br1 - bfhi(pCim) * bi1; w1im = bfhi(pCre) * bi1 + bfhi(pCim) * br1;
  }
  float mx = fmaxf(fmaxf(fabsf(w0re), fabsf(w0im)), fmaxf(fabsf(w1re), fabsf(w1im)));
#pragma unroll
  for (int o = 16; o > 0; o >>= 1) mx = fmaxf(mx, __shfl_xor_sync(0xffffffffu, mx, o));
  int ex = (__float_as_uint(mx) >> 23) & 0xff;
  ex = min(max(ex, 1), 252);
  const float scale = __uint_as_float((uint32_t)(253 - ex) << 23);
  const float inv_scale = __uint_as_float((uint32_t)(ex + 1) << 23);

  float acc[5][4];
#pragma unroll
  for (int i = 0; i < 5; i++) { acc[i][0] = acc[i][1] = acc[i][2] = acc[i][3] = 0.f; }
  float k2048 = 0.f;
  unsigned char* tabw = sm + SB_TAB + w * SB_WREG;
  const uint32_t ldA = sbase + SB_TAB + w * SB_WREG + ((lane & 7) + 8 * ((lane >> 4) & 1)) * 112 + ((lane >> 3) & 1) * 16;
  const uint32_t ldB = sbase + SB_TAB + w * SB_WREG + ((lane & 7) + 8 * ((lane >> 3) & 1)) * 112 + 32 + (lane >> 4) * 16;
#pragma unroll 1
  for (int r = 0; r < 2; r++) {
    {
      const float a2 = dt * (r ? bfhi(pAre) : bflo(pAre)) * 1.4426950408889634f;
      const float bt = dt * (r ? bfhi(pAim) : bflo(pAim)) * 0.15915494309189535f;
      cplx W; W.re = (r ? w1re : w0re) * scale; W.im = -(r ? w1im : w0im) * scale;
      unsigned char* rec = tabw + ((lane >> 3) * 16 + (lane & 7)) * 112;
      const cplx y1 = zpow_acc(a2, -bt, 1.f), z8 = zpow_acc(a2, bt, 8.f), y128 = zpow_acc(a2, -bt, 128.f);
      const cplx y512 = zpow_acc(a2, -bt, 512.f), y1024 = zpow_acc(a2, -bt, 1024.f);
      const cplx z16 = csq(z8), z32 = csq(z16), z64 = csq(z32);
      const cplx y2 = csq(y1), y4 = csq(y2), y256 = csq(y128);
      cplx one; one.re = 1.f; one.im = 0.f;
      const hc h16 = bcast(z16), h32 = bcast(z32), h2 = bcast(y2), h4 = bcast(y4);
      const hc h128 = bcast(y128), h256 = bcast(y256), h512 = bcast(y512);
      gen8(rec, one, z8, h16, h32);
      gen8(rec + 16, z64, z8, h16, h32);
      gen8(rec + 32, W, y1, h2, h4);
      gen8(rec + 48, cmul(W, y128), y1, h2, h4);
      gen8(rec + 64, cmul(W, y256), y2, h4, h128);
      gen8(rec + 80, cmul(W, y512), y128, h256, h4);
      const cplx w1024 = cmul(W, y1024);
      gen8(rec + 96, w1024, y128, h256, h512);
      k2048 += w1024.re * y1024.re - w1024.im * y1024.im;
    }
    __syncwarp();
#pragma unroll
    for (int ks = 0; ks < 4; ks++) {
      uint32_t a0, a1, a2, a3, b0, b1, b2, b3;
      ldsm_x4_t(ldA + ks * 1792, a0, a1, a2, a3);
      ldsm_x4_t(ldB + ks * 1792, b0, b1, b2, b3);
      mma_f16(acc[0], a0, a1, a2, a3, b0, b1);
      mma_f16(acc[1], a0, a1, a2, a3, b2, b3);
      ldsm_x4_t(ldB + ks * 1792 + 32, b0, b1, b2, b3);
      mma_f16(acc[2], a0, a1, a2, a3, b0, b1);
      mma_f16(acc[3], a0, a1, a2, a3, b2, b3);
      ldsm_x2_t(ldB + ks * 1792 + 64, b0, b1);
      mma_f16(acc[4], a0, a1, a2, a3, b0, b1);
    }
    __syncwarp();
  }
  {
    float* red = reinterpret_cast<float*>(tabw);
#pragma unroll
    for (int hr = 0; hr < 2; hr++) {
      const int row = g + 8 * hr;
      *reinterpret_cast<float2*>(red + 8 * row + 2 * t) = make_float2(acc[0][2 * hr] * inv_scale, acc[0][2 * hr + 1] * inv_scale);
      *reinterpret_cast<float2*>(red + 128 + 8 * row + 2 * t) = make_float2(acc[1][2 * hr] * inv_scale, acc[1][2 * hr + 1] * inv_scale);
      *reinterpret_cast<float2*>(red + 256 + 64 * (t >> 1) + 2 * (t & 1) + 4 * row) = make_float2(acc[2][2 * hr] * inv_scale, acc[2][2 * hr + 1] * inv_scale);
      red[384 + 64 * (t & 1) + (t >> 1) + 2 * row] = acc[3][2 * hr] * inv_scale;
      red[384 + 64 * (t & 1) + 32 + (t >> 1) + 2 * row] = acc[3][2 * hr + 1] * inv_scale;
      red[512 + 32 * t + row] = acc[4][2 * hr] * inv_scale;
      red[512 + 32 * t + 16 + row] = acc[4][2 * hr + 1] * inv_scale;
    }
#pragma unroll
    for (int o = 16; o > 0; o >>= 1) k2048 += __shfl_xor_sync(0xffffffffu, k2048, o);
    if (lane == 0) red[640] = k2048 * inv_scale;
  }
  const uint32_t ubar = smem_u32(smem_all) + FR_BAR + (upper ? 8 : 0);
  const int ustg = upper ? FR_LN : FR_CS;
  if ((threadIdx.x & 255) == 0) {
    mbar_init(ubar, 1);
    asm volatile("fence.mbarrier_init.release.cluster;" ::: "memory");
    flag_wait(&g_cnt[7], (__ldcg(&g_epoch) + 1u) * 128u);
    asm volatile("fence.proxy.async;" ::: "memory");
    mbar_expect(ubar, 16384);
    tma2d(smem_u32(smem_all) + ustg, &tmU, ubar, (blockIdx.x * 4 + (sub & 2)) * 16, 0);
    tma2d(smem_u32(smem_all) + FR_X + (upper ? 8192 : 0), &tmX, ubar, (blockIdx.x * 4 + (sub & 2)) * 16, 0);
  }
  __syncwarp();
  named_bar(bar, 128);
  float* Kv = reinterpret_cast<float*>(sm + SB_KV);
  {
    const float* r0 = reinterpret_cast<const float*>(sm + SB_TAB);
    constexpr int WS = SB_WREG / 4;
    const float4 a = *reinterpret_cast<const float4*>(r0 + 4 * tid), b = *reinterpret_cast<const float4*>(r0 + WS + 4 * tid);
    const float4 c = *reinterpret_cast<const float4*>(r0 + 2 * WS + 4 * tid), e = *reinterpret_cast<const float4*>(r0 + 3 * WS + 4 * tid);
    *reinterpret_cast<float4*>(Kv + 4 * tid) =
        make_float4((a.x + b.x) + (c.x + e.x), (a.y + b.y) + (c.y + e.y), (a.z + b.z) + (c.z + e.z), (a.w + b.w) + (c.w + e.w));
    const int i = 512 + tid;
    Kv[i] = (r0[i] + r0[WS + i]) + (r0[2 * WS + i] + r0[3 * WS + i]);
    if (tid == 0) Kv[640] = (r0[640] + r0[WS + 640]) + (r0[2 * WS + 640] + r0[3 * WS + 640]);
  }
  named_bar(bar, 128);
  {
    auto tap_idx = [](int j) { const int m = j >> 1; const int r = (j & 1) ? m + (m & 1) : m; return min(max(j < 256 ? j : 128 + r, 0), 640); };
    float kd[3][3], f3[3], f2[3];
#pragma unroll
    for (int it = 0; it < 3; it++) {
      const int j = 528 - 2 * (tid + 128 * it);
#pragma unroll
      for (int e = 0; e < 3; e++) kd[it][e] = Kv[tap_idx(j + 1 - e)];
    }
    const int fa = tid >= 48, xa = tid - 48 * fa, ja = 144 - 2 * xa;
    const int fb = tid >> 6, xb = tid & 63, jb = 160 - 2 * xb;
#pragma unroll
    for (int e = 0; e < 3; e++) {
      f3[e] = Kv[min(max(384 + fa + 2 * (ja + 1 - e), 0), 640)];
      f2[e] = Kv[min(256 + fb + 2 * (jb + 1 - e), 640)];
    }
    const float k512 = Kv[384];
    uint32_t* ee = reinterpret_cast<uint32_t*>(sm + SB_KD);
#pragma unroll
    for (int it = 0; it < 3; it++) {
      const int x = tid + 128 * it, j = 528 - 2 * x;
      const float k0 = (j >= -1 && j <= 508) ? kd[it][0] : 0.f;
      float k1 = (j >= 0 && j <= 510) ? kd[it][1] : 0.f;
      const float k2 = (j >= 1 && j <= 510) ? kd[it][2] : 0.f;
      if (j == 510) k1 -= k512;
      const uint32_t we = pack_bf16(k1, k2), wo = pack_bf16(k0, k1);
      if (x < 272) { ee[2 * x] = we; ee[560 + 2 * x] = wo; }
      if (x < 272 && x >= 4) { ee[2 * x - 7] = we; ee[560 + 2 * x - 7] = wo; }
    }
    {
      const int hi = 128 - fa;
      const float k0 = (ja + 1 >= 64 && ja + 1 <= hi) ? f3[0] : 0.f, k1 = (ja >= 64 && ja <= hi) ? f3[1] : 0.f;
      const float k2 = (ja - 1 >= 64 && ja - 1 <= hi) ? f3[2] : 0.f;
      const uint32_t we = pack_bf16(k1, k2), wo = pack_bf16(k0, k1);
      uint32_t* p = reinterpret_cast<uint32_t*>(sm + SB_F3) + fa * 224;
      if (tid < 96) { p[2 * xa] = we; p[112 + 2 * xa] = wo; }
      if (tid < 96 && xa < 44) { p[2 * xa + 9] = we; p[112 + 2 * xa + 9] = wo; }
    }
    {
      const float k0 = (jb + 1 >= 64 && jb + 1 <= 127) ? f2[0] : 0.f, k1 = (jb >= 64 && jb <= 127) ? f2[1] : 0.f;
      const float k2 = (jb - 1 >= 64 && jb - 1 <= 127) ? f2[2] : 0.f;
      const uint32_t we = pack_bf16(k1, k2), wo = pack_bf16(k0, k1);
      uint32_t* p = reinterpret_cast<uint32_t*>(sm + SB_F2) + fb * 288;
      p[2 * xb] = we; p[144 + 2 * xb] = wo;
      p[2 * xb + 17] = we; p[144 + 2 * xb + 17] = wo;
    }
  }
  const float k1024 = Kv[512];
  named_bar(hbar, 256);
  mbar_wait(ubar, 0);
#pragma unroll
  for (int k = 0; k < 2; k++) {
    const int c = tid + 128 * k;
    *reinterpret_cast<uint4*>(sm + SB_U + rowaddr((c >> 1) + UZ) + (c & 1) * 16) =
        *reinterpret_cast<const uint4*>(smem_all + ustg + (c >> 1) * 64 + (sub & 1) * 32 + (c & 1) * 16);
  }
  named_bar(hbar, 256);
  const int krow = (lane & 7) + 8 * ((lane >> 3) & 1);
  if (w < 2) {
    float acd[4][2][4];
#pragma unroll
    for (int c = 0; c < 4; c++)
#pragma unroll
      for (int i = 0; i < 2; i++)
#pragma unroll
        for (int e = 0; e < 4; e++) acd[c][i][e] = 0.f;
    const uint32_t aQ = sbase + SB_U + rowaddr(UZ + 64 * w + 4 * krow) + (lane >> 4) * 16;
    const uint32_t pb = sbase + ((g & 1) ? SB_KDO + ((529 - g) / 2 + t) * 8 : SB_KD + ((528 - g) / 2 + t) * 8);
    uint32_t Q[36][4];
#define QOFF(j) (32 * (j) + 16 * (((j) + 64) / 4 - 16))
#pragma unroll
    for (int n = 0; n < 5; n++) ldsm_x4(aQ + QOFF(3 - n), Q[n][0], Q[n][1], Q[n][2], Q[n][3]);
#pragma unroll
    for (int q = 0; q < 33; q++) {
      if (q + 5 < 36) ldsm_x4(aQ + QOFF(3 - (q + 5)), Q[q + 5][0], Q[q + 5][1], Q[q + 5][2], Q[q + 5][3]);
      const uint2 e0 = lds64(pb - 32 * (2 * q));
      const uint2 e1 = lds64(pb - 32 * (2 * q + 1));
#pragma unroll
      for (int c = 0; c < 4; c++) {
        mma_bf16(acd[c][0], Q[3 - c + q][0], Q[3 - c + q][1], Q[3 - c + q][2], Q[3 - c + q][3], e0.x, e0.y);
        mma_bf16(acd[c][1], Q[3 - c + q][0], Q[3 - c + q][1], Q[3 - c + q][2], Q[3 - c + q][3], e1.x, e1.y);
      }
    }
#undef QOFF
    const int yl = (64 * (16 * w + g) + 2 * t + 16 * (g & 1) + 8 * ((g >> 1) & 1)) * 4;
    unsigned char* yb = sm + SB_Y + 8192;
#pragma unroll
    for (int c = 0; c < 4; c++)
#pragma unroll
      for (int nu = 0; nu < 2; nu++)
#pragma unroll
        for (int hr = 0; hr < 2; hr++)
          *reinterpret_cast<float2*>(yb + ((yl ^ ((16 * c + 8 * (nu ^ (c >> 1))) * 4)) + hr * 2048)) = make_float2(acd[c][nu][2 * hr], acd[c][nu][2 * hr + 1]);
  } else {
    const int yl = (16 * (g ^ ((g >> 2) & 1)) + 2 * t + 8 * ((g >> 1) & 1)) * 4;
    if (w == 2) {
      float ac[7][2][4];
#pragma unroll
      for (int T = 0; T < 7; T++)
#pragma unroll
        for (int i = 0; i < 2; i++)
#pragma unroll
          for (int e = 0; e < 4; e++) ac[T][i][e] = 0.f;
      uint32_t BA[2][4];
#pragma unroll
      for (int ks = 0; ks < 2; ks++)
#pragma unroll
        for (int r = 0; r < 4; r++) {
          uint32_t v = 0;
#pragma unroll
          for (int e = 0; e < 2; e++) {
            const int dlt = (2 * t + e + 8 * (r >> 1) + 16 * ks - 8) - g;
            const bool on = (r & 1) ? (dlt >= -5 && dlt <= -3) : (dlt >= -2 && dlt <= 2);
            v |= on ? (0x3f80u << (16 * e)) : 0u;
          }
          BA[ks][r] = v;
        }
      const int chl = 2 * UZ + (lane & 7) + (lane >> 3) - 1;
      const uint32_t ub = sbase + SB_U + rowaddr(chl >> 1) + (chl & 1) * 16;
      const uint32_t fb = sbase + SB_F2 + (80 - (g - t)) * 8;
#pragma unroll
      for (int sp = 0; sp < 2; sp++) {
        uint32_t bb[2][7][2];
#pragma unroll
        for (int i = 0; i < 7 - sp; i++) {
          const int beta = 11 - sp - 2 * i;
#pragma unroll
          for (int o = 0; o < 2; o++) {
            uint32_t u0, u1, u2, u3;
            ldsm_x4(ub + (2 * beta + o) * 144, u0, u1, u2, u3);
            float z[4] = {0.f, 0.f, 0.f, 0.f};
            mma_bf16(z, BA[0][0], BA[0][1], BA[0][2], BA[0][3], u0, u1);
            mma_bf16(z, BA[1][0], BA[1][1], BA[1][2], BA[1][3], u2, u3);
            bb[0][i][o] = pack_bf16(z[0], z[1]);
            bb[1][i][o] = pack_bf16(z[2], z[3]);
          }
        }
#pragma unroll
        for (int f = 0; f < 2; f++) {
#pragma unroll
          for (int k = 0; k < 3; k++) {
#pragma unroll
            for (int nu = 0; nu < 2; nu++) {
              const uint2 A01 = lds64(fb + f * 1152 + nu * 576 - 32 * (6 + 2 * (2 * k + sp)));
              const uint2 A23 = lds64(fb + f * 1152 + nu * 576 - 32 * (5 + 2 * (2 * k + sp)));
#pragma unroll
              for (int i = 0; i < 7 - sp; i++) {
                const int T = 7 - i + k;
                if (T <= 7) mma_bf16(ac[T - 1][nu], A01.x, A01.y, A23.x, A23.y, bb[f][i][0], bb[f][i][1]);
              }
            }
          }
        }
      }
      named_bar(5 + bar, 96);
      unsigned char* yb = sm + SB_Y;
#pragma unroll
      for (int T = 0; T <= 7; T++)
#pragma unroll
        for (int nu = 0; nu < 2; nu++)
#pragma unroll
          for (int hr = 0; hr < 2; hr++)
            *reinterpret_cast<float2*>(yb + ((yl ^ ((8 * (nu ^ hr)) * 4)) + (16 * T + 8 * hr) * 64)) =
                T ? make_float2(ac[T ? T - 1 : 0][nu][2 * hr], ac[T ? T - 1 : 0][nu][2 * hr + 1]) : make_float2(0.f, 0.f);
    } else {
      float ac[5][2][4];
#pragma unroll
      for (int T = 0; T < 5; T++)
#pragma unroll
        for (int i = 0; i < 2; i++)
#pragma unroll
          for (int e = 0; e < 4; e++) ac[T][i][e] = 0.f;
      const uint32_t fb = sbase + SB_F3 + ((g & 1) ? 448 + ((145 - g) / 2 + t) * 8 : ((144 - g) / 2 + t) * 8);
      uint32_t ur[3];
#pragma unroll
      for (int sg = 0; sg < 3; sg++) ur[sg] = sbase + SB_U + rowaddr(UZ + (lane & 7) + 8 * (lane >> 4) + sg - 1) + ((lane >> 3) & 1) * 16;
#pragma unroll 1
      for (int f = 0; f < 2; f++) {
        uint32_t BA[3][4];
        const int lo = f ? -11 : -4, hi = f ? -5 : 4;
#pragma unroll
        for (int sg = 0; sg < 3; sg++)
#pragma unroll
          for (int r = 0; r < 4; r++) {
            uint32_t v = 0;
#pragma unroll
            for (int e = 0; e < 2; e++) {
              const int dlt = (2 * t + e + 8 * (r >> 1) + 16 * (sg - 1)) - (g + 8 * (r & 1));
              v |= (dlt >= lo && dlt <= hi) ? (0x3f80u << (16 * e)) : 0u;
            }
            BA[sg][r] = v;
          }
        uint2 A01[5], A23[5];
#pragma unroll
        for (int s = 0; s < 5; s++) {
          A01[s] = lds64(fb + f * 896 - 32 * (8 + 2 * s));
          A23[s] = lds64(fb + f * 896 - 32 * (7 + 2 * s));
        }
#pragma unroll
        for (int beta = 3; beta >= -1; beta--) {
          float z0[4] = {0.f, 0.f, 0.f, 0.f}, z1[4] = {0.f, 0.f, 0.f, 0.f};
#pragma unroll
          for (int sg = 0; sg < 3; sg++) {
            uint32_t u0, u1, u2, u3;
            ldsm_x4(ur[sg] + beta * 576, u0, u1, u2, u3);
            mma_bf16(z0, BA[sg][0], BA[sg][1], BA[sg][2], BA[sg][3], u0, u1);
            mma_bf16(z1, BA[sg][0], BA[sg][1], BA[sg][2], BA[sg][3], u2, u3);
          }
          const uint32_t b0 = pack_bf16(z0[0], z0[1]), b1 = pack_bf16(z1[0], z1[1]);
          const uint32_t b2 = pack_bf16(z0[2], z0[3]), b3 = pack_bf16(z1[2], z1[3]);
#pragma unroll
          for (int s = 0; s < 5; s++) {
            const int T = beta + 4 + s;
            if (T <= 7) {
              mma_bf16(ac[T - 3][0], A01[s].x, A01[s].y, A23[s].x, A23[s].y, b0, b1);
              mma_bf16(ac[T - 3][1], A01[s].x, A01[s].y, A23[s].x, A23[s].y, b2, b3);
            }
          }
        }
      }
      {
        const uint32_t nk = (uint32_t)__bfloat16_as_ushort(__float2bfloat16_rn(-k1024));
        uint32_t PC[5];
#pragma unroll
        for (int m = 0; m < 5; m++) {
          const int j = 8 * (125 + m) + g - 2 * t;
          PC[m] = ((j == 1020 || j == 1021) ? nk : 0u) | ((j == 1021 || j == 1022) ? (nk << 16) : 0u);
        }
#pragma unroll
        for (int k = 0; k < 2; k++) {
          const uint32_t ab = sbase + SB_U + rowaddr(UZ + 48 - 63 - k + krow) + (lane >> 4) * 16;
#pragma unroll
          for (int T = 3; T <= 7; T++) {
            uint32_t a0, a1, a2, a3;
            ldsm_x4(ab + (T - 3) * 576, a0, a1, a2, a3);
            mma_bf16(ac[T - 3][0], a0, a1, a2, a3, PC[1 + 2 * k], PC[2 * k]);
            mma_bf16(ac[T - 3][1], a0, a1, a2, a3, PC[2 + 2 * k], PC[1 + 2 * k]);
          }
        }
      }
      unsigned char* yb = sm + SB_Y + 16384;
#pragma unroll
      for (int T = 0; T <= 7; T++)
#pragma unroll
        for (int nu = 0; nu < 2; nu++)
#pragma unroll
          for (int hr = 0; hr < 2; hr++)
            *reinterpret_cast<float2*>(yb + ((yl ^ ((8 * (nu ^ hr)) * 4)) + (16 * T + 8 * hr) * 64)) =
                T >= 3 ? make_float2(ac[T >= 3 ? T - 3 : 0][nu][2 * hr], ac[T >= 3 ? T - 3 : 0][nu][2 * hr + 1]) : make_float2(0.f, 0.f);
    }
  }
  if (w < 2) asm volatile("bar.arrive %0, 96;" ::"r"(5 + bar) : "memory");
  named_bar(bar, 128);
  {
    const __nv_bfloat162 ds = *reinterpret_cast<const __nv_bfloat162*>(&dsk2);
    const int r0 = tid >> 2, ch = tid & 3;
    const int yo = (16 * (r0 ^ ((r0 >> 2) & 1)) + ((4 * ch) ^ (8 * (((r0 >> 1) ^ (r0 >> 3)) & 1)))) * 4;
    const int uo = SB_U + rowaddr(r0 + UZ) + ch * 8;
#pragma unroll
    for (int k = 0; k < 4; k++) {
      const float4 a = *reinterpret_cast<const float4*>(sm + SB_Y + yo + k * 2048);
      const float4 b = *reinterpret_cast<const float4*>(sm + SB_Y + 8192 + yo + k * 2048);
      const float4 c = *reinterpret_cast<const float4*>(sm + SB_Y + 16384 + yo + k * 2048);
      const uint2 uw = *reinterpret_cast<const uint2*>(sm + uo + k * 1152);
      const uint2 xw = *reinterpret_cast<const uint2*>(smem_all + FR_X + (sub >> 1) * 8192 + r0 * 64 + (sub & 1) * 32 + ch * 8 + k * 2048);
      const uint32_t y0 = pack_bf16(b.x + (a.x + c.x), b.y + (a.y + c.y)), y1 = pack_bf16(b.z + (a.z + c.z), b.w + (a.w + c.w));
      const __nv_bfloat162 h0 = __hadd2_rn(*reinterpret_cast<const __nv_bfloat162*>(&xw.x),
          __hadd2_rn(*reinterpret_cast<const __nv_bfloat162*>(&y0), __hmul2_rn(*reinterpret_cast<const __nv_bfloat162*>(&uw.x), ds)));
      const __nv_bfloat162 h1 = __hadd2_rn(*reinterpret_cast<const __nv_bfloat162*>(&xw.y),
          __hadd2_rn(*reinterpret_cast<const __nv_bfloat162*>(&y1), __hmul2_rn(*reinterpret_cast<const __nv_bfloat162*>(&uw.y), ds)));
      *reinterpret_cast<uint2*>(g_hT + (size_t)d * SEQ + tid * 4 + k * 512) =
          make_uint2(*reinterpret_cast<const uint32_t*>(&h0), *reinterpret_cast<const uint32_t*>(&h1));
    }
  }
  named_bar(hbar, 256);
  if ((threadIdx.x & 255) == 0) {
    __threadfence();
    asm volatile("red.relaxed.gpu.global.add.u32 [%0], 1;" ::"l"(&g_cnt[blockIdx.x >> 4]) : "memory");
  }
}

constexpr int M_A     = 0;
constexpr int M_W     = 7 * 16384;
constexpr int M_XB    = M_W + 3 * 32768;
constexpr int M_CS    = M_XB + 14336;
constexpr int M_BAR   = M_CS + 1792;
constexpr int M_TOTAL = M_BAR + 384;

__device__ __forceinline__ float sigmoid_fast(float x) {
  float th; asm("tanh.approx.f32 %0, %1;" : "=f"(th) : "f"(0.5f * x));
  return fmaf(0.5f, th, 0.5f);
}
template <int NCB, int NA, int OFS>
__device__ __forceinline__ void g1_pack(const float (&acc)[NA], uint32_t* pk, const float* cs,
                                        float mb0, float rs0, float mb1, float rs1, int lane) {
  const int t = lane & 3;
  const float c0 = -mb0 * rs0, c1 = -mb1 * rs1;
#pragma unroll
  for (int cb = 0; cb < NCB; cb++) {
    const float2 sc = *reinterpret_cast<const float2*>(cs + cb * 8 + 2 * t);
    pk[2 * cb]     = pack_bf16(fmaf(acc[OFS + 4 * cb + 0], rs0, c0 * sc.x), fmaf(acc[OFS + 4 * cb + 1], rs0, c0 * sc.y));
    pk[2 * cb + 1] = pack_bf16(fmaf(acc[OFS + 4 * cb + 2], rs1, c1 * sc.x), fmaf(acc[OFS + 4 * cb + 3], rs1, c1 * sc.y));
  }
}
__device__ __forceinline__ uint32_t glu2(uint32_t gw, uint32_t uw) {
  return pack_bf16(sigmoid_fast(bflo(gw)) * bflo(uw), sigmoid_fast(bfhi(gw)) * bfhi(uw));
}
__device__ __forceinline__ uint32_t w2_slot(int j, int kp) {
  const int sl = j % 10;
  if (sl < 6) return M_W + ((sl >> 1) + 2) % 3 * 32768 + (sl & 1) * 16384;
  const int i = sl - 6;
  return M_A + (i + (i >= kp ? 3 : 0)) * 16384;
}

__global__ void __cluster_dims__(2, 1, 1) __launch_bounds__(384, 1)
k_mlp(const __grid_constant__ CUtensorMap tmA, const __grid_constant__ CUtensorMap tmG,
      const __grid_constant__ CUtensorMap tmU, const __grid_constant__ CUtensorMap tmD, bf16* __restrict__ out) {
  extern __shared__ __align__(1024) unsigned char smem[];
  const uint32_t sb = smem_u32(smem);
  const int tid = threadIdx.x, lane = tid & 31, warp = tid >> 5;
  const uint32_t rank = blockIdx.x & 1;
  const bool live = blockIdx.x >= 4;
  const int pr = live ? (blockIdx.x - 4) >> 1 : 0;
  const int mt = pr & 15;
  const int fp = pr >> 4;
  const int fj = 4 * rank + fp;
  const int kp = min((112 * fp) >> 6, 4);
  const uint32_t barA = sb + M_BAR, barF = barA + 56, barE = barF + 24, barS = barE + 24;
  const uint32_t barW2 = barS + 8, barAf = barW2 + 112, barX = barAf + 8, barH = barX + 8, barE2 = barH + 16;
  if (tid == 288 || tid == 289) prefetch_tm(tid == 288 ? &tmA : &tmD);
  if (lane == 0 && warp < 5) {
#pragma unroll
    for (int i = 0; i < 8; i++) {
      const int b = warp * 8 + i;
      if (b < 36 && (b < 7 || b >= 10)) mbar_init(barA + 8 * b, ((b >= 10 && b < 13) || b == 28 || b >= 32) ? 2 : (b == 29 ? 4 : 1));
    }
    asm volatile("fence.mbarrier_init.release.cluster;" ::: "memory");
    if (sb & 1023) __trap();
  }
  if (tid == 256) {
    for (int s = 0; s < 3; s++) mbar_init(barF + 8 * s, 1);
    asm volatile("fence.mbarrier_init.release.cluster;" ::: "memory");
    for (int s = 0; s < (live ? 3 : 0); s++) {
      mbar_expect(barF + 8 * s, 32768);
      const uint32_t dst = sb + M_W + s * 32768;
      tma2d(dst, &tmG, barF + 8 * s, 224 * fj, 64 * s);
      tma2d(dst + 16384, &tmU, barF + 8 * s, 224 * fj, 64 * s);
      tma2d(dst + 8192, &tmG, barF + 8 * s, 224 * fj + 64, 64 * s);
      tma2d(dst + 24576, &tmU, barF + 8 * s, 224 * fj + 64, 64 * s);
    }
  }
  __syncthreads();
  cluster_arrive();

  if (warp >= 8) {
    const unsigned int ep = __ldcg(&g_epoch);
    asm volatile("setmaxnreg.dec.sync.aligned.u32 24;");
    if (!live) {
      cluster_wait();
      if (warp == 9) { named_bar(2, 288); named_bar(3, 288); }
    } else if (warp == 8) {
      if (lane == 0) {
        for (int it = 3; it < 14; it++) {
          const int s = it % 3, rnd = it / 3;
          const bool pb = it >= 7;
          const int kb = pb ? it - 7 : it;
          if (rnd > 0) mbar_wait(barE + 8 * s, (rnd - 1) & 1);
          mbar_expect(barF + 8 * s, 32768);
          const uint32_t dst = sb + M_W + s * 32768;
          const int c0 = 224 * fj + (pb ? 128 : 0);
          tma2d(dst, &tmG, barF + 8 * s, c0, 64 * kb);
          tma2d(dst + 16384, &tmU, barF + 8 * s, c0, 64 * kb);
          tma2d(dst + 8192, &tmG, barF + 8 * s, c0 + 64, 64 * kb);
          tma2d(dst + 24576, &tmU, barF + 8 * s, c0 + 64, 64 * kb);
        }
        for (int j = 0; j < 14; j++) {
          if (j < 6 && !(j & 1)) { const int it = 11 + (j >> 1); mbar_wait(barE + 8 * (it % 3), (it / 3) & 1); }
          if (j == 6) mbar_wait(barAf, 0);
          if (j >= 10) mbar_wait(barE2 + 8 * (j - 10), 0);
          mbar_expect(barW2 + 8 * j, 16384);
          const uint32_t dst = sb + w2_slot(j, kp);
#pragma unroll
          for (int h = 0; h < 2; h++) {
            const int u = 2 * j + h;
            int c, o;
            if (u < 7) { c = 0; o = u; } else if (u < 19) { c = 1 + (u - 7) / 4; o = (u - 7) % 4; } else { c = 1 + (u - 19) / 3; o = 4 + (u - 19) % 3; }
            const int row = (4 * rank + ((fp + c) & 3)) * 224 + 32 * o;
            tma2d(dst + h * 4096, &tmD, barW2 + 8 * j, 112 * fp, row);
            tma2d(dst + 8192 + h * 4096, &tmD, barW2 + 8 * j, 112 * fp + 64, row);
          }
        }
      }
      __syncwarp();
      cluster_wait();
    } else if (warp == 9) {
      if (lane < 7) flag_wait(&g_cnt[lane], (ep + 1u) * 32u);
      cluster_wait();
      if (lane == 0) {
        asm volatile("fence.proxy.async;" ::: "memory");
        for (int k = 0; k < 7; k++) {
          mbar_expect(barA + 8 * k, 16384);
          tma3d_mc(sb + M_A + k * 16384 + rank * 8192, &tmA, barA + 8 * k, 0, 64 * k, 2 * mt + rank, (uint16_t)3);
        }
      }
      __syncwarp();
#pragma unroll 1
      for (int p = 0; p < 2; p++) {
        named_bar(2 + p, 288);
        if (lane == 0) {
          asm volatile("fence.acq_rel.gpu;" ::: "memory");
          asm volatile("red.relaxed.gpu.global.add.u32 [%0], 1;" ::"l"(&g_cnt2[(mt * 2 + rank) * 2 + p]) : "memory");
        }
        __syncwarp();
      }
    } else if (warp == 10) {
      cluster_wait();
      if (lane == 0) {
#pragma unroll 1
        for (int p = 0; p < 2; p++) {
          flag_wait(&g_cnt2[(mt * 2 + rank) * 2 + p], (ep + 1u) * 4u);
          mbar_arrive(barH + 8 * p);
        }
      }
    } else {
      if (lane == 0) flag_wait(&g_cnt[8], (ep + 1u) * 40u);
      __syncwarp();
      float* cs = reinterpret_cast<float*>(smem + M_CS);
      for (int i = lane; i < 448; i += 32) cs[i] = __ldcg(&g_cs[(i >= 224 ? FF + i - 224 : i) + fj * 224]);
      __syncwarp();
      if (lane == 0) mbar_arrive(barS);
      cluster_wait();
    }
    __syncwarp();
    cluster_arrive(); cluster_wait();
  } else {
    asm volatile("setmaxnreg.inc.sync.aligned.u32 240;");
    const int wg = warp >> 2, wq = warp & 3;
    const bool elect = (tid & 127) == 0;
    const float* cs = reinterpret_cast<const float*>(smem + M_CS);
#define RELEASE(b) do { if (elect) mbar_arrive(b); } while (0)
#define PUBLISH(p) asm volatile("bar.arrive %0, 288;" ::"r"(2 + (p)) : "memory")
    const int dr = (lane & 7) + 8 * (lane >> 4), tc = 2 * wq + ((lane >> 3) & 1);
    const uint32_t aT = sb + M_A + wg * 8192 + dr * 128 + ((tc ^ (lane & 7)) << 4);
    uint4* hbase = reinterpret_cast<uint4*>(g_P) + (size_t)(mt * 8 * 8 + warp) * (14 * 32) + lane;
    const uint32_t dead = live ? 0u : 1u;
    float mb0, rs0, mb1, rs1;
    uint32_t pkA[64];
    {
      float accA[128];
      float s0 = 0.f, q0 = 0.f, s1 = 0.f, q1 = 0.f;
#pragma unroll
      for (int kb = 0; kb < 7; kb++) {
        const int s = kb % 3;
        mbar_wait(barA + 8 * kb, (0) | dead);
        uint32_t af[4][4];
#pragma unroll
        for (int k = 0; k < 4; k++) ldsm_x4_t(aT + kb * 16384 + k * 2048, af[k][0], af[k][1], af[k][2], af[k][3]);
        mbar_wait(barF + 8 * s, ((kb / 3) & 1) | dead);
        const uint64_t db = mk_desc(sb + M_W + s * 32768, 8192, 1024, 1);
        wg_fence();
#pragma unroll
        for (int k = 0; k < 4; k++) wgmma_rs_n256(accA, af[k][0], af[k][1], af[k][2], af[k][3], db + k * 128, (kb | k) != 0);
        wg_commit();
        if (kb > 0) { wg_wait<1>(); RELEASE(barE + 8 * ((kb - 1) % 3)); }
#pragma unroll
        for (int k = 0; k < 4; k++) {
#pragma unroll
          for (int h = 0; h < 2; h++) {
            const float a = bflo(af[k][2 * h]), b = bfhi(af[k][2 * h]), c = bflo(af[k][2 * h + 1]), e = bfhi(af[k][2 * h + 1]);
            s0 += a + b; q0 = fmaf(a, a, fmaf(b, b, q0));
            s1 += c + e; q1 = fmaf(c, c, fmaf(e, e, q1));
          }
        }
      }
#pragma unroll
      for (int o = 1; o <= 2; o <<= 1) {
        s0 += __shfl_xor_sync(0xffffffffu, s0, o); q0 += __shfl_xor_sync(0xffffffffu, q0, o);
        s1 += __shfl_xor_sync(0xffffffffu, s1, o); q1 += __shfl_xor_sync(0xffffffffu, q1, o);
      }
      s0 *= (1.0f / DM); s1 *= (1.0f / DM);
      mb0 = bf16r(s0); mb1 = bf16r(s1);
      rs0 = __fdiv_rn(1.0f, bf16r(sqrtf(bf16r(bf16r(fmaxf(q0 * (1.0f / DM) - s0 * s0, 0.f)) + 1e-5f))));
      rs1 = __fdiv_rn(1.0f, bf16r(sqrtf(bf16r(bf16r(fmaxf(q1 * (1.0f / DM) - s1 * s1, 0.f)) + 1e-5f))));
      mbar_wait(barS, (0) | dead);
      wg_wait<0>();
      RELEASE(barE + 0);
      g1_pack<16, 128, 0>(accA, pkA, cs, mb0, rs0, mb1, rs1, lane);
      g1_pack<16, 128, 64>(accA, pkA + 32, cs + 224, mb0, rs0, mb1, rs1, lane);
    }
    uint32_t hf[56];
    uint32_t pkB[48];
    uint4* hown = live ? hbase + (size_t)fj * (8 * 14 * 32) : reinterpret_cast<uint4*>(g_dummy) + lane;
    {
      float accG[48], accU[48];
#pragma unroll
      for (int kb = 0; kb < 7; kb++) {
        const int it = kb + 7, s = it % 3;
        uint32_t af[4][4];
#pragma unroll
        for (int k = 0; k < 4; k++) ldsm_x4_t(aT + kb * 16384 + k * 2048, af[k][0], af[k][1], af[k][2], af[k][3]);
        mbar_wait(barF + 8 * s, ((it / 3) & 1) | dead);
        const uint64_t db = mk_desc(sb + M_W + s * 32768, 8192, 1024, 1);
        wg_fence();
#pragma unroll
        for (int k = 0; k < 4; k++) {
          wgmma_rs_n96(accG, af[k][0], af[k][1], af[k][2], af[k][3], db + k * 128, (kb | k) != 0);
          wgmma_rs_n96(accU, af[k][0], af[k][1], af[k][2], af[k][3], db + 1024 + k * 128, (kb | k) != 0);
        }
        wg_commit();
        if (kb > 0) { wg_wait<1>(); RELEASE(barE + 8 * ((it - 1) % 3)); }
        if (kb < 4) {
#pragma unroll
          for (int i = 0; i < 8; i++) hf[8 * kb + i] = glu2(pkA[8 * kb + i], pkA[32 + 8 * kb + i]);
          hown[(2 * kb) * 32] = make_uint4(hf[8 * kb], hf[8 * kb + 1], hf[8 * kb + 2], hf[8 * kb + 3]);
          hown[(2 * kb + 1) * 32] = make_uint4(hf[8 * kb + 4], hf[8 * kb + 5], hf[8 * kb + 6], hf[8 * kb + 7]);
          if (kb == 3) PUBLISH(0);
        }
      }
      wg_wait<0>();
      if (elect) { mbar_arrive(barE + 8 * (13 % 3)); mbar_arrive(barAf); }
      g1_pack<12, 48, 0>(accG, pkB, cs + 128, mb0, rs0, mb1, rs1, lane);
      g1_pack<12, 48, 0>(accU, pkB + 24, cs + 352, mb0, rs0, mb1, rs1, lane);
    }
#pragma unroll
    for (int i = 0; i < 24; i++) hf[32 + i] = glu2(pkB[i], pkB[24 + i]);
#pragma unroll
    for (int q = 0; q < 6; q++) hown[(8 + q) * 32] = make_uint4(hf[32 + 4 * q], hf[33 + 4 * q], hf[34 + 4 * q], hf[35 + 4 * q]);
    PUBLISH(1);
    float acc[56];
    auto hsrc = [&](int i) -> const uint4* {
      int c, o;
      if (i < 38) { c = 1 + (i - 14) / 8; o = (i - 14) % 8; } else { c = 1 + (i - 38) / 6; o = 8 + (i - 38) % 6; }
      return hbase + (size_t)(4 * rank + ((fp + c) & 3)) * (8 * 14 * 32) + o * 32;
    };
    uint4 hq[4][4];
#pragma unroll
    for (int j = 0; j < 14; j++) {
      if (j == 1) mbar_wait(barH, dead);
      if (j == 7) mbar_wait(barH + 8, dead);
#pragma unroll
      for (int k = 0; k < 4; k++) {
        const int i = 4 * (j + 2) + k;
        if (i >= 14 && i < 56) hq[(j + 2) & 3][k] = __ldcg(hsrc(i));
      }
      mbar_wait(barW2 + 8 * j, (0) | dead);
      const uint64_t db = mk_desc(sb + w2_slot(j, kp), 8192, 1024, 1);
      wg_fence();
#pragma unroll
      for (int k = 0; k < 4; k++) {
        const int i = 4 * j + k;
        if (i < 14) wgmma_rs_n112(acc, hf[4 * i], hf[4 * i + 1], hf[4 * i + 2], hf[4 * i + 3], db + k * 128, i != 0);
        else wgmma_rs_n112(acc, hq[j & 3][k].x, hq[j & 3][k].y, hq[j & 3][k].z, hq[j & 3][k].w, db + k * 128, 1);
      }
      wg_commit();
      if (j > 0) { wg_wait<1>(); if (j <= 4) RELEASE(barE2 + 8 * (j - 1)); }
    }
    wg_wait<0>();
    cluster_wait();
    if (wg != (int)rank) {
      asm volatile("bar.arrive 1, 256;" ::: "memory");
      const uint32_t xd = mapa(sb + M_XB, rank ^ 1) + (tid & 127) * 16;
#pragma unroll
      for (int q = 0; q < 7; q++)
        asm volatile("st.shared::cluster.v4.b32 [%0], {%1,%2,%3,%4};" ::"r"(xd + q * 2048), "r"(pack_bf16(acc[8 * q], acc[8 * q + 1])),
                     "r"(pack_bf16(acc[8 * q + 2], acc[8 * q + 3])), "r"(pack_bf16(acc[8 * q + 4], acc[8 * q + 5])),
                     "r"(pack_bf16(acc[8 * q + 6], acc[8 * q + 7])) : "memory");
      __syncwarp();
      if (lane == 0) asm volatile("mbarrier.arrive.release.cluster.shared::cluster.b64 _, [%0];" ::"r"(mapa(barX, rank ^ 1)) : "memory");
    } else {
      uint32_t hr[7][4];
      const int d0 = 112 * fp;
#pragma unroll
      for (int q = 0; q < 7; q++) {
        const int dd = d0 + 16 * q;
        ldsm_x4_t(aT + (dd >> 6) * 16384 + (dd & 63) * 128, hr[q][0], hr[q][1], hr[q][2], hr[q][3]);
      }
      { uint32_t ok; int it = 0;
        do { asm volatile("{.reg .pred p; mbarrier.try_wait.parity.acquire.cluster.shared::cta.b64 p, [%1], 0; selp.u32 %0,1,0,p;}"
                          : "=r"(ok) : "r"(barX) : "memory"); } while (!ok && ++it < (1 << 24)); }
      const uint32_t stg = sb + M_W + wq * 3840;
      const uint32_t so = stg + ((lane & 7) + 8 * ((lane >> 3) & 1)) * 240 + (lane >> 4) * 16;
      named_bar(1, 256);
#pragma unroll
      for (int q = 0; q < 7; q++) {
        const uint4 v = *reinterpret_cast<const uint4*>(smem + M_XB + q * 2048 + (tid & 127) * 16);
        const uint32_t m0 = pack_bf16(acc[8 * q] + bflo(v.x), acc[8 * q + 1] + bfhi(v.x)), m1 = pack_bf16(acc[8 * q + 2] + bflo(v.y), acc[8 * q + 3] + bfhi(v.y));
        const uint32_t m2 = pack_bf16(acc[8 * q + 4] + bflo(v.z), acc[8 * q + 5] + bfhi(v.z)), m3 = pack_bf16(acc[8 * q + 6] + bflo(v.w), acc[8 * q + 7] + bfhi(v.w));
        stsm_x4(so + q * 32, pack_bf16(bflo(hr[q][0]) + bflo(m0), bfhi(hr[q][0]) + bfhi(m0)), pack_bf16(bflo(hr[q][1]) + bflo(m1), bfhi(hr[q][1]) + bfhi(m1)),
                pack_bf16(bflo(hr[q][2]) + bflo(m2), bfhi(hr[q][2]) + bfhi(m2)), pack_bf16(bflo(hr[q][3]) + bflo(m3), bfhi(hr[q][3]) + bfhi(m3)));
      }
      __syncwarp();
      bf16* o = live ? out + (size_t)(mt * 128 + 64 * wg + 16 * wq) * DM + d0 : g_dummy;
#pragma unroll
      for (int k = 0; k < 7; k++) {
        const int c = lane + 32 * k;
        const int r = c / 14, ch = c - 14 * r;
        *reinterpret_cast<uint4*>(o + (size_t)r * DM + ch * 8) = *reinterpret_cast<const uint4*>(smem + M_W + wq * 3840 + r * 240 + ch * 16);
      }
    }
    if (tid == 0 && live) {
      const unsigned int n = atomicAdd(&g_done, 1u);
      if ((n & 127u) == 127u) atomicAdd(&g_epoch, 1u);
    }
    __syncwarp();
    cluster_arrive(); cluster_wait();
#undef PUBLISH
#undef RELEASE
  }
}

typedef CUresult (*EncFn)(CUtensorMap*, CUtensorMapDataType, cuuint32_t, void*, const cuuint64_t*, const cuuint64_t*,
                          const cuuint32_t*, const cuuint32_t*, CUtensorMapInterleave, CUtensorMapSwizzle,
                          CUtensorMapL2promotion, CUtensorMapFloatOOBfill);

static void make_map(EncFn enc, CUtensorMap* tm, const void* ptr, int rank, const uint64_t* dims, const uint64_t* strides_bytes,
                     const uint32_t* box, CUtensorMapSwizzle swz) {
  cuuint64_t gd[3], gs[2]; cuuint32_t bd[3], es[3] = {1, 1, 1};
  for (int i = 0; i < rank; i++) { gd[i] = dims[i]; bd[i] = box[i]; }
  for (int i = 0; i < rank - 1; i++) gs[i] = strides_bytes[i];
  enc(tm, CU_TENSOR_MAP_DATA_TYPE_BFLOAT16, rank, const_cast<void*>(ptr), gd, gs, bd, es, CU_TENSOR_MAP_INTERLEAVE_NONE, swz,
      CU_TENSOR_MAP_L2_PROMOTION_L2_128B, CU_TENSOR_MAP_FLOAT_OOB_FILL_NONE);
}

template <class K, class... Args>
static void launch_k(K kern, int grid, int block, int smem, bool pdl, Args... args) {
  cudaLaunchConfig_t cfg = {};
  cfg.gridDim = dim3(grid); cfg.blockDim = dim3(block); cfg.dynamicSmemBytes = smem; cfg.stream = cudaStreamPerThread;
  cudaLaunchAttribute at[1];
  at[0].id = cudaLaunchAttributeProgrammaticStreamSerialization;
  at[0].val.programmaticStreamSerializationAllowed = 1;
  cfg.attrs = at; cfg.numAttrs = pdl ? 1 : 0;
  cudaLaunchKernelEx(&cfg, kern, args...);
}

extern "C" void kernel_launch(void* const* d_in, const int* in_sizes, int n_in, void* d_out, int out_size) {
  const bf16* x   = (const bf16*)d_in[0];
  const bf16* Are = (const bf16*)d_in[1];
  const bf16* Aim = (const bf16*)d_in[2];
  const bf16* Bre = (const bf16*)d_in[3];
  const bf16* Bim = (const bf16*)d_in[4];
  const bf16* Cre = (const bf16*)d_in[5];
  const bf16* Cim = (const bf16*)d_in[6];
  const bf16* ldt = (const bf16*)d_in[7];
  const bf16* dsk = (const bf16*)d_in[8];
  const bf16* wg  = (const bf16*)d_in[10];
  const bf16* wu  = (const bf16*)d_in[11];
  const bf16* wd  = (const bf16*)d_in[12];

  static EncFn enc = nullptr;
  static void *p_hT = nullptr, *p_uT = nullptr, *p_xT = nullptr;
  if (!enc) {
    void* fn = nullptr; cudaDriverEntryPointQueryResult qr;
    cudaGetDriverEntryPoint("cuTensorMapEncodeTiled", &fn, cudaEnableDefault, &qr);
    enc = (EncFn)fn;
    cudaGetSymbolAddress(&p_hT, g_hT);
    cudaGetSymbolAddress(&p_uT, g_uT);
    cudaGetSymbolAddress(&p_xT, g_xT);
    cudaFuncSetAttribute(k_ssm, cudaFuncAttributeMaxDynamicSharedMemorySize, FRONT_SMEM);
    cudaFuncSetAttribute(k_mlp, cudaFuncAttributeMaxDynamicSharedMemorySize, M_TOTAL);
  }
  CUtensorMap tmA, tmG, tmU, tmD, tmLu, tmLx;
  {
    uint64_t dims[2] = {DM * 16, SEQ / 16}, st[1] = {DM * 32};
    uint32_t box[2] = {32, 128};
    make_map(enc, &tmLu, p_uT, 2, dims, st, box, CU_TENSOR_MAP_SWIZZLE_NONE);
    make_map(enc, &tmLx, p_xT, 2, dims, st, box, CU_TENSOR_MAP_SWIZZLE_NONE);
  }
  {
    uint64_t dims[3] = {64, DM, SEQ / 64}, st[2] = {SEQ * 2, 128};
    uint32_t box[3] = {64, 64, 1};
    make_map(enc, &tmA, p_hT, 3, dims, st, box, CU_TENSOR_MAP_SWIZZLE_128B);
  }
  {
    uint64_t dims[2] = {FF, DM}, st[1] = {FF * 2};
    uint32_t box[2] = {64, 64};
    make_map(enc, &tmG, wg, 2, dims, st, box, CU_TENSOR_MAP_SWIZZLE_128B);
    make_map(enc, &tmU, wu, 2, dims, st, box, CU_TENSOR_MAP_SWIZZLE_128B);
  }
  {
    uint64_t dims[2] = {DM, FF}, st[1] = {DM * 2};
    uint32_t box[2] = {64, 32};
    make_map(enc, &tmD, wd, 2, dims, st, box, CU_TENSOR_MAP_SWIZZLE_128B);
  }
  launch_k(k_ssm, 132, 512, FRONT_SMEM, false, Are, Aim, Bre, Bim, Cre, Cim, ldt, dsk, x, wg, wu, wd, tmLu, tmLx);
  launch_k(k_mlp, 132, 384, M_TOTAL, true, tmA, tmG, tmU, tmD, (bf16*)d_out);
}
```

```cpp
#include <cuda_runtime.h>
#include <cuda_bf16.h>
#include <cuda_fp16.h>
#include <cuda.h>
#include <stdint.h>

typedef __nv_bfloat16 bf16;

constexpr int SEQ = 2048;
constexpr int DM  = 448;
constexpr int NM  = 256;
constexpr int FF  = 1792;

__device__ __align__(1024) bf16  g_uT[DM * SEQ];
__device__ __align__(1024) bf16  g_xT[DM * SEQ];
__device__ __align__(1024) bf16  g_hT[DM * SEQ];
__device__ __align__(1024) bf16  g_P[SEQ * FF];
__device__ __align__(1024) bf16  g_dummy[16 * DM];
__device__ __align__(1024) float g_cs[2 * FF];

__device__ __forceinline__ uint32_t smem_u32(const void* p) { return (uint32_t)__cvta_generic_to_shared(p); }
__device__ __forceinline__ float bf16r(float v) { return __bfloat162float(__float2bfloat16_rn(v)); }
__device__ __forceinline__ float bflo(uint32_t w) { return __uint_as_float(w << 16); }
__device__ __forceinline__ float bfhi(uint32_t w) { return __uint_as_float(w & 0xffff0000u); }
__device__ __forceinline__ uint32_t pack_bf16(float lo, float hi) {
  uint32_t r; asm("cvt.rn.bf16x2.f32 %0, %1, %2;" : "=r"(r) : "f"(hi), "f"(lo)); return r;
}
__device__ __forceinline__ uint32_t pack_f16(float lo, float hi) {
  uint32_t r; asm("cvt.rn.f16x2.f32 %0, %1, %2;" : "=r"(r) : "f"(hi), "f"(lo)); return r;
}
__device__ __forceinline__ float ex2f(float x) { float r; asm("ex2.approx.ftz.f32 %0, %1;" : "=f"(r) : "f"(x)); return r; }
__device__ __forceinline__ void pdl_launch() { asm volatile("griddepcontrol.launch_dependents;"); }
__device__ __forceinline__ void pdl_wait() { asm volatile("griddepcontrol.wait;" ::: "memory"); }

__device__ __forceinline__ void mbar_init(uint32_t a, int c) { asm volatile("mbarrier.init.shared::cta.b64 [%0], %1;" ::"r"(a), "r"(c)); }
__device__ __forceinline__ void mbar_expect(uint32_t a, uint32_t bytes) {
  asm volatile("mbarrier.arrive.expect_tx.shared::cta.b64 _, [%0], %1;" ::"r"(a), "r"(bytes) : "memory");
}
__device__ __forceinline__ void mbar_arrive(uint32_t a) { asm volatile("mbarrier.arrive.shared::cta.b64 _, [%0];" ::"r"(a) : "memory"); }
__device__ __forceinline__ void mbar_arrive_cluster(uint32_t remote_a) {
  asm volatile("mbarrier.arrive.shared::cluster.b64 _, [%0];" ::"r"(remote_a) : "memory");
}
__device__ __forceinline__ void mbar_wait(uint32_t a, uint32_t ph) {
  uint32_t ok; int it = 0;
  do {
    asm volatile("{.reg .pred p; mbarrier.try_wait.parity.shared::cta.b64 p, [%1], %2; selp.u32 %0,1,0,p;}"
                 : "=r"(ok) : "r"(a), "r"(ph) : "memory");
  } while (!ok && ++it < (1 << 24));
}
__device__ __forceinline__ void flag_wait(const unsigned int* p, unsigned int target) {
  unsigned int v; int it = 0;
  asm volatile("ld.acquire.gpu.global.u32 %0, [%1];" : "=r"(v) : "l"(p) : "memory");
  if ((int)(v - target) >= 0) return;
  while (true) {
    __nanosleep(32);
    asm volatile("ld.relaxed.gpu.global.u32 %0, [%1];" : "=r"(v) : "l"(p) : "memory");
    if ((int)(v - target) >= 0 || ++it > (1 << 22)) break;
  }
  asm volatile("ld.acquire.gpu.global.u32 %0, [%1];" : "=r"(v) : "l"(p) : "memory");
}
__device__ __forceinline__ uint4 ld_relaxed_v4(const uint4* p) {
  uint4 v; asm volatile("ld.relaxed.gpu.global.v4.u32 {%0,%1,%2,%3}, [%4];" : "=r"(v.x), "=r"(v.y), "=r"(v.z), "=r"(v.w) : "l"(p) : "memory"); return v;
}
__device__ __forceinline__ void st_relaxed_v4(uint4* p, uint32_t a, uint32_t b, uint32_t c, uint32_t d) {
  asm volatile("st.relaxed.gpu.global.v4.u32 [%0], {%1,%2,%3,%4};" ::"l"(p), "r"(a), "r"(b), "r"(c), "r"(d) : "memory");
}
__device__ __forceinline__ uint32_t mapa(uint32_t a, uint32_t rank) {
  uint32_t r; asm volatile("mapa.shared::cluster.u32 %0, %1, %2;" : "=r"(r) : "r"(a), "r"(rank)); return r;
}
__device__ __forceinline__ void cluster_arrive() { asm volatile("barrier.cluster.arrive.release.aligned;" ::: "memory"); }
__device__ __forceinline__ void cluster_wait() { asm volatile("barrier.cluster.wait.acquire.aligned;" ::: "memory"); }
__device__ __forceinline__ void fence_async() { asm volatile("fence.proxy.async.shared::cta;" ::: "memory"); }
__device__ __forceinline__ void named_bar(int id, int n) { asm volatile("bar.sync %0, %1;" ::"r"(id), "r"(n) : "memory"); }

__device__ __forceinline__ void tma2d(uint32_t dst, const CUtensorMap* tm, uint32_t bar, int c0, int c1) {
  asm volatile("cp.async.bulk.tensor.2d.shared::cluster.global.mbarrier::complete_tx::bytes [%0], [%1, {%3,%4}], [%2];"
               ::"r"(dst), "l"(tm), "r"(bar), "r"(c0), "r"(c1) : "memory");
}
__device__ __forceinline__ void tma3d(uint32_t dst, const CUtensorMap* tm, uint32_t bar, int c0, int c1, int c2) {
  asm volatile("cp.async.bulk.tensor.3d.shared::cluster.global.mbarrier::complete_tx::bytes [%0], [%1, {%3,%4,%5}], [%2];"
               ::"r"(dst), "l"(tm), "r"(bar), "r"(c0), "r"(c1), "r"(c2) : "memory");
}
__device__ __forceinline__ void tma3d_mc(uint32_t dst, const CUtensorMap* tm, uint32_t bar, int c0, int c1, int c2, uint16_t mask) {
  asm volatile("cp.async.bulk.tensor.3d.shared::cluster.global.mbarrier::complete_tx::bytes.multicast::cluster [%0], [%1, {%3,%4,%5}], [%2], %6;"
               ::"r"(dst), "l"(tm), "r"(bar), "r"(c0), "r"(c1), "r"(c2), "h"(mask) : "memory");
}
__device__ __forceinline__ void tma2d_store(const CUtensorMap* tm, uint32_t src, int c0, int c1) {
  asm volatile("cp.async.bulk.tensor.2d.global.shared::cta.bulk_group [%0, {%2,%3}], [%1];"
               ::"l"(tm), "r"(src), "r"(c0), "r"(c1) : "memory");
}
__device__ __forceinline__ void bulk_commit() { asm volatile("cp.async.bulk.commit_group;" ::: "memory"); }
template <int N> __device__ __forceinline__ void bulk_wait_read() { asm volatile("cp.async.bulk.wait_group.read %0;" ::"n"(N) : "memory"); }
template <int N> __device__ __forceinline__ void bulk_wait() { asm volatile("cp.async.bulk.wait_group %0;" ::"n"(N) : "memory"); }
__device__ __forceinline__ void prefetch_tm(const CUtensorMap* tm) { asm volatile("prefetch.tensormap [%0];" ::"l"(tm) : "memory"); }

__device__ __forceinline__ void wg_fence() { asm volatile("wgmma.fence.sync.aligned;" ::: "memory"); }
__device__ __forceinline__ void wg_commit() { asm volatile("wgmma.commit_group.sync.aligned;" ::: "memory"); }
template <int N> __device__ __forceinline__ void wg_wait() { asm volatile("wgmma.wait_group.sync.aligned %0;" ::"n"(N) : "memory"); }
__device__ __forceinline__ uint64_t mk_desc(uint32_t addr, uint32_t lbo, uint32_t sbo, uint32_t swz) {
  return (uint64_t)((addr & 0x3FFFF) >> 4) | ((uint64_t)(lbo >> 4) << 16) | ((uint64_t)(sbo >> 4) << 32) | ((uint64_t)swz << 62);
}
__device__ __forceinline__ void ldsm_x4(uint32_t a, uint32_t& r0, uint32_t& r1, uint32_t& r2, uint32_t& r3) {
  asm volatile("ldmatrix.sync.aligned.m8n8.x4.shared.b16 {%0,%1,%2,%3}, [%4];" : "=r"(r0), "=r"(r1), "=r"(r2), "=r"(r3) : "r"(a));
}
__device__ __forceinline__ void ldsm_x4_t(uint32_t a, uint32_t& r0, uint32_t& r1, uint32_t& r2, uint32_t& r3) {
  asm volatile("ldmatrix.sync.aligned.m8n8.x4.trans.shared.b16 {%0,%1,%2,%3}, [%4];" : "=r"(r0), "=r"(r1), "=r"(r2), "=r"(r3) : "r"(a));
}
__device__ __forceinline__ void ldsm_x2_t(uint32_t a, uint32_t& r0, uint32_t& r1) {
  asm volatile("ldmatrix.sync.aligned.m8n8.x2.trans.shared.b16 {%0,%1}, [%2];" : "=r"(r0), "=r"(r1) : "r"(a));
}
__device__ __forceinline__ void stsm_x4(uint32_t a, uint32_t r0, uint32_t r1, uint32_t r2, uint32_t r3) {
  asm volatile("stmatrix.sync.aligned.m8n8.x4.shared.b16 [%0], {%1,%2,%3,%4};" ::"r"(a), "r"(r0), "r"(r1), "r"(r2), "r"(r3) : "memory");
}
__device__ __forceinline__ void stsm_x2(uint32_t a, uint32_t r0, uint32_t r1) {
  asm volatile("stmatrix.sync.aligned.m8n8.x2.shared.b16 [%0], {%1,%2};" ::"r"(a), "r"(r0), "r"(r1) : "memory");
}
__device__ __forceinline__ uint32_t lds32(uint32_t a) { uint32_t r; asm volatile("ld.shared.u32 %0, [%1];" : "=r"(r) : "r"(a)); return r; }
__device__ __forceinline__ void mma_bf16(float (&c)[4], uint32_t a0, uint32_t a1, uint32_t a2, uint32_t a3, uint32_t b0, uint32_t b1) {
  asm volatile("mma.sync.aligned.m16n8k16.row.col.f32.bf16.bf16.f32 {%0,%1,%2,%3}, {%4,%5,%6,%7}, {%8,%9}, {%0,%1,%2,%3};"
               : "+f"(c[0]), "+f"(c[1]), "+f"(c[2]), "+f"(c[3]) : "r"(a0), "r"(a1), "r"(a2), "r"(a3), "r"(b0), "r"(b1));
}
__device__ __forceinline__ void mma_f16(float (&c)[4], uint32_t a0, uint32_t a1, uint32_t a2, uint32_t a3, uint32_t b0, uint32_t b1) {
  asm volatile("mma.sync.aligned.m16n8k16.row.col.f32.f16.f16.f32 {%0,%1,%2,%3}, {%4,%5,%6,%7}, {%8,%9}, {%0,%1,%2,%3};"
               : "+f"(c[0]), "+f"(c[1]), "+f"(c[2]), "+f"(c[3]) : "r"(a0), "r"(a1), "r"(a2), "r"(a3), "r"(b0), "r"(b1));
}
__device__ __forceinline__ void cp_async16(uint32_t dst, const void* src) {
  asm volatile("cp.async.cg.shared.global [%0], [%1], 16;" ::"r"(dst), "l"(src) : "memory");
}
__device__ __forceinline__ void cp_async_wait_all() { asm volatile("cp.async.wait_all;" ::: "memory"); }

__device__ unsigned int g_epoch;
__device__ unsigned int g_cnt[16];
__device__ unsigned int g_cnt2[256];
__device__ unsigned int g_done;

constexpr int LN_PITCH = 912;
constexpr int LN_STAT  = 16 * LN_PITCH;
constexpr int LN_SMEM  = LN_STAT + 7 * 128;
__device__ __forceinline__ void ln1_load(const bf16* __restrict__ x, int tile, unsigned char* sm) {
  const int r = (threadIdx.x >> 4) & 15, c = threadIdx.x & 15;
  const uint32_t dst = smem_u32(sm) + r * LN_PITCH + c * 16;
  const bf16* src = x + (size_t)(tile * 16 + r) * DM + c * 8;
#pragma unroll
  for (int k = 0; k < 4; k++)
    if (k < 3 || c < 8) cp_async16(dst + k * 256, src + k * 128);
}
__device__ __forceinline__ void ln1_tile(int tile, unsigned char* sm) {
  const uint32_t sb = smem_u32(sm);
  const int lane = threadIdx.x & 31, w = (threadIdx.x >> 5) - 8;
  const int g = lane >> 2, t = lane & 3;
  cp_async_wait_all();
  named_bar(14, 256);
  if (w < 7) {
    float s1[4] = {0.f, 0.f, 0.f, 0.f}, qa[4] = {0.f, 0.f, 0.f, 0.f}, qb[4] = {0.f, 0.f, 0.f, 0.f};
    const uint32_t ad = sb + ((lane & 7) + 8 * ((lane >> 3) & 1)) * LN_PITCH + (lane >> 4) * 16 + w * 128;
#pragma unroll
    for (int k = 0; k < 4; k++) {
      uint32_t a0, a1, a2, a3;
      ldsm_x4(ad + k * 32, a0, a1, a2, a3);
      mma_bf16(s1, a0, a1, a2, a3, 0x3f803f80u, 0x3f803f80u);
      mma_bf16(qa, a0, a1, a2, a3, a0, a2);
      mma_bf16(qb, a0, a1, a2, a3, a1, a3);
    }
    if (t == (g >> 1)) {
      float2* st = reinterpret_cast<float2*>(sm + LN_STAT) + w * 16;
      st[g]     = make_float2(s1[0], (g & 1) ? qa[1] : qa[0]);
      st[g + 8] = make_float2(s1[2], (g & 1) ? qb[3] : qb[2]);
    }
  }
  named_bar(14, 256);
  if (w < 7) {
    float mb[4], rd[4];
    {
      const float2* st = reinterpret_cast<const float2*>(sm + LN_STAT) + (lane & 15);
      float sx = 0.f, sy = 0.f;
#pragma unroll
      for (int i = 0; i < 7; i++) { const float2 p = st[16 * i]; sx += p.x; sy += p.y; }
      const float mean = sx * (1.0f / DM);
      const float var = fmaxf(sy * (1.0f / DM) - mean * mean, 0.f);
      const float m = bf16r(mean);
      const float r = __fdiv_rn(1.0f, bf16r(sqrtf(bf16r(bf16r(var) + 1e-5f))));
#pragma unroll
      for (int e = 0; e < 4; e++) {
        mb[e] = __shfl_sync(0xffffffffu, m, 4 * t + e);
        rd[e] = __shfl_sync(0xffffffffu, r, 4 * t + e);
      }
    }
    const int r8 = lane & 7;
    const int tok = 4 * (r8 >> 1) + (r8 & 1) + 2 * ((lane >> 3) & 1);
    const uint32_t ad = sb + tok * LN_PITCH + (w * 64 + (lane >> 4) * 8) * 2;
    const size_t go = (size_t)(tile * DM + w * 64 + g) * 16 + 4 * t;
#pragma unroll
    for (int k = 0; k < 4; k++) {
      uint32_t v[4];
      ldsm_x4_t(ad + k * 32, v[0], v[1], v[2], v[3]);
#pragma unroll
      for (int h = 0; h < 2; h++) {
        const uint32_t d0 = pack_bf16(bflo(v[2 * h]) - mb[0], bfhi(v[2 * h]) - mb[1]);
        const uint32_t d1 = pack_bf16(bflo(v[2 * h + 1]) - mb[2], bfhi(v[2 * h + 1]) - mb[3]);
        const size_t o = go + (size_t)(16 * k + 8 * h) * 16;
        *reinterpret_cast<uint2*>(g_uT + o) = make_uint2(pack_bf16(bflo(d0) * rd[0], bfhi(d0) * rd[1]), pack_bf16(bflo(d1) * rd[2], bfhi(d1) * rd[3]));
        *reinterpret_cast<uint2*>(g_xT + o) = make_uint2(v[2 * h], v[2 * h + 1]);
      }
    }
    asm volatile("bar.arrive 12, 256;" ::: "memory");
  } else {
    named_bar(12, 256);
    if (lane == 0) {
      __threadfence();
      asm volatile("red.relaxed.gpu.global.add.u32 [%0], 1;" ::"l"(&g_cnt[7]) : "memory");
    }
    __syncwarp();
  }
}

constexpr int CS_SMEM = 448 * 64 + 16 * 128;
__device__ __forceinline__ void colsum_load(const bf16* __restrict__ wg, const bf16* __restrict__ wu, int b2, unsigned char* sm) {
  const bf16* W = (b2 >= 56 ? wu : wg) + (b2 % 56) * 32;
  const uint32_t sb = smem_u32(sm);
#pragma unroll
  for (int k = 0; k < 7; k++)
    cp_async16(sb + (threadIdx.x & 255) * 16 + k * 4096, W + (size_t)((threadIdx.x & 255) >> 2) * FF + (threadIdx.x & 3) * 8 + (size_t)k * 64 * FF);
}
__device__ __forceinline__ void colsum_reduce(unsigned char* sm) {
  const int lane = threadIdx.x & 31, w = (threadIdx.x >> 5) & 7;
  if (w >= 7) return;
  float acc[4][4];
#pragma unroll
  for (int i = 0; i < 4; i++) { acc[i][0] = acc[i][1] = acc[i][2] = acc[i][3] = 0.f; }
  const uint32_t ad = smem_u32(sm) + (w * 64 + (lane & 15)) * 64 + (lane >> 4) * 16;
#pragma unroll
  for (int k = 0; k < 4; k++) {
#pragma unroll
    for (int h = 0; h < 2; h++) {
      uint32_t b0, b1, b2, b3;
      ldsm_x4_t(ad + k * 1024 + h * 32, b0, b1, b2, b3);
      mma_bf16(acc[2 * h], 0x3f803f80u, 0x3f803f80u, 0x3f803f80u, 0x3f803f80u, b0, b1);
      mma_bf16(acc[2 * h + 1], 0x3f803f80u, 0x3f803f80u, 0x3f803f80u, 0x3f803f80u, b2, b3);
    }
  }
  if (lane < 4) {
    float* sf = reinterpret_cast<float*>(sm + 448 * 64) + w * 32 + 2 * lane;
#pragma unroll
    for (int i = 0; i < 4; i++) *reinterpret_cast<float2*>(sf + 8 * i) = make_float2(acc[i][0], acc[i][1]);
  }
}
__device__ __forceinline__ void colsum_store(int b2, unsigned char* sm) {
  const float* sf = reinterpret_cast<const float*>(sm + 448 * 64);
  const int lane = threadIdx.x & 31;
  float s = 0.f;
#pragma unroll
  for (int i = 0; i < 7; i++) s += sf[i * 32 + lane];
  g_cs[(b2 >= 56 ? FF : 0) + (b2 % 56) * 32 + lane] = s;
}
__device__ __forceinline__ void wgmma_rs_n96(float (&d)[48], uint32_t a0, uint32_t a1, uint32_t a2, uint32_t a3, uint64_t db, int sc) {
  asm volatile("{\n.reg .pred p;\nsetp.ne.b32 p, %53, 0;\n"
    "wgmma.mma_async.sync.aligned.m64n96k16.f32.bf16.bf16 {%0, %1, %2, %3, %4, %5, %6, %7, %8, %9, %10, %11, %12, %13, %14, %15, %16, %17, %18, %19, %20, %21, %22, %23, %24, %25, %26, %27, %28, %29, %30, %31, %32, %33, %34, %35, %36, %37, %38, %39, %40, %41, %42, %43, %44, %45, %46, %47}, {%48, %49, %50, %51}, %52, p, 1, 1, 1;\n}\n"
    : "+f"(d[0]), "+f"(d[1]), "+f"(d[2]), "+f"(d[3]), "+f"(d[4]), "+f"(d[5]), "+f"(d[6]), "+f"(d[7]), "+f"(d[8]), "+f"(d[9]), "+f"(d[10]), "+f"(d[11]), "+f"(d[12]), "+f"(d[13]), "+f"(d[14]), "+f"(d[15]), "+f"(d[16]), "+f"(d[17]), "+f"(d[18]), "+f"(d[19]), "+f"(d[20]), "+f"(d[21]), "+f"(d[22]), "+f"(d[23]), "+f"(d[24]), "+f"(d[25]), "+f"(d[26]), "+f"(d[27]), "+f"(d[28]), "+f"(d[29]), "+f"(d[30]), "+f"(d[31]), "+f"(d[32]), "+f"(d[33]), "+f"(d[34]), "+f"(d[35]), "+f"(d[36]), "+f"(d[37]), "+f"(d[38]), "+f"(d[39]), "+f"(d[40]), "+f"(d[41]), "+f"(d[42]), "+f"(d[43]), "+f"(d[44]), "+f"(d[45]), "+f"(d[46]), "+f"(d[47])
    : "r"(a0), "r"(a1), "r"(a2), "r"(a3), "l"(db), "r"(sc));
}
__device__ __forceinline__ void wgmma_rs_n128(float (&d)[64], uint32_t a0, uint32_t a1, uint32_t a2, uint32_t a3, uint64_t db, int sc) {
  asm volatile("{\n.reg .pred p;\nsetp.ne.b32 p, %69, 0;\n"
    "wgmma.mma_async.sync.aligned.m64n128k16.f32.bf16.bf16 {%0, %1, %2, %3, %4, %5, %6, %7, %8, %9, %10, %11, %12, %13, %14, %15, %16, %17, %18, %19, %20, %21, %22, %23, %24, %25, %26, %27, %28, %29, %30, %31, %32, %33, %34, %35, %36, %37, %38, %39, %40, %41, %42, %43, %44, %45, %46, %47, %48, %49, %50, %51, %52, %53, %54, %55, %56, %57, %58, %59, %60, %61, %62, %63}, {%64, %65, %66, %67}, %68, p, 1, 1, 1;\n}\n"
    : "+f"(d[0]), "+f"(d[1]), "+f"(d[2]), "+f"(d[3]), "+f"(d[4]), "+f"(d[5]), "+f"(d[6]), "+f"(d[7]), "+f"(d[8]), "+f"(d[9]), "+f"(d[10]), "+f"(d[11]), "+f"(d[12]), "+f"(d[13]), "+f"(d[14]), "+f"(d[15]), "+f"(d[16]), "+f"(d[17]), "+f"(d[18]), "+f"(d[19]), "+f"(d[20]), "+f"(d[21]), "+f"(d[22]), "+f"(d[23]), "+f"(d[24]), "+f"(d[25]), "+f"(d[26]), "+f"(d[27]), "+f"(d[28]), "+f"(d[29]), "+f"(d[30]), "+f"(d[31]), "+f"(d[32]), "+f"(d[33]), "+f"(d[34]), "+f"(d[35]), "+f"(d[36]), "+f"(d[37]), "+f"(d[38]), "+f"(d[39]), "+f"(d[40]), "+f"(d[41]), "+f"(d[42]), "+f"(d[43]), "+f"(d[44]), "+f"(d[45]), "+f"(d[46]), "+f"(d[47]), "+f"(d[48]), "+f"(d[49]), "+f"(d[50]), "+f"(d[51]), "+f"(d[52]), "+f"(d[53]), "+f"(d[54]), "+f"(d[55]), "+f"(d[56]), "+f"(d[57]), "+f"(d[58]), "+f"(d[59]), "+f"(d[60]), "+f"(d[61]), "+f"(d[62]), "+f"(d[63])
    : "r"(a0), "r"(a1), "r"(a2), "r"(a3), "l"(db), "r"(sc));
}
__device__ __forceinline__ void wgmma_rs_n112(float (&d)[56], uint32_t a0, uint32_t a1, uint32_t a2, uint32_t a3, uint64_t db, int sc) {
  asm volatile("{\n.reg .pred p;\nsetp.ne.b32 p, %61, 0;\n"
    "wgmma.mma_async.sync.aligned.m64n112k16.f32.bf16.bf16 {%0, %1, %2, %3, %4, %5, %6, %7, %8, %9, %10, %11, %12, %13, %14, %15, %16, %17, %18, %19, %20, %21, %22, %23, %24, %25, %26, %27, %28, %29, %30, %31, %32, %33, %34, %35, %36, %37, %38, %39, %40, %41, %42, %43, %44, %45, %46, %47, %48, %49, %50, %51, %52, %53, %54, %55}, {%56, %57, %58, %59}, %60, p, 1, 1, 1;\n}\n"
    : "+f"(d[0]), "+f"(d[1]), "+f"(d[2]), "+f"(d[3]), "+f"(d[4]), "+f"(d[5]), "+f"(d[6]), "+f"(d[7]), "+f"(d[8]), "+f"(d[9]), "+f"(d[10]), "+f"(d[11]), "+f"(d[12]), "+f"(d[13]), "+f"(d[14]), "+f"(d[15]), "+f"(d[16]), "+f"(d[17]), "+f"(d[18]), "+f"(d[19]), "+f"(d[20]), "+f"(d[21]), "+f"(d[22]), "+f"(d[23]), "+f"(d[24]), "+f"(d[25]), "+f"(d[26]), "+f"(d[27]), "+f"(d[28]), "+f"(d[29]), "+f"(d[30]), "+f"(d[31]), "+f"(d[32]), "+f"(d[33]), "+f"(d[34]), "+f"(d[35]), "+f"(d[36]), "+f"(d[37]), "+f"(d[38]), "+f"(d[39]), "+f"(d[40]), "+f"(d[41]), "+f"(d[42]), "+f"(d[43]), "+f"(d[44]), "+f"(d[45]), "+f"(d[46]), "+f"(d[47]), "+f"(d[48]), "+f"(d[49]), "+f"(d[50]), "+f"(d[51]), "+f"(d[52]), "+f"(d[53]), "+f"(d[54]), "+f"(d[55])
    : "r"(a0), "r"(a1), "r"(a2), "r"(a3), "l"(db), "r"(sc));
}

struct cplx { float re, im; };
__device__ __forceinline__ cplx cmul(cplx a, cplx b) {
  cplx r; r.re = a.re * b.re - a.im * b.im; r.im = a.re * b.im + a.im * b.re; return r;
}
__device__ __forceinline__ cplx zpow_acc(float a2, float bt, float c) {
  float mag = ex2f(a2 * c);
  float tr = bt * c;
  tr -= rintf(tr);
  float ang = tr * 6.283185307179586f;
  cplx r; r.re = mag * __cosf(ang); r.im = mag * __sinf(ang); return r;
}

constexpr int SB_TAB  = 0;
constexpr int SB_WREG = 7168;
constexpr int UZ = 40;
constexpr int SB_U    = 4 * SB_WREG;
constexpr int SB_KV   = SB_U + 172 * 36;
constexpr int SB_TOTAL = (SB_KV + 644 * 4 + 127) / 128 * 128;
constexpr int SB_F3   = 0;
constexpr int SB_F2   = 1792;
constexpr int SB_Y    = 4096;
constexpr int SB_KD   = SB_Y;
constexpr int SB_KDO  = SB_KD + 2240;
constexpr int FR_LN = 4 * SB_TOTAL;
constexpr int FR_CS = (FR_LN + LN_SMEM + 127) / 128 * 128;
constexpr int FR_X = FR_CS + CS_SMEM;
constexpr int FRONT_SMEM = FR_X + 16384;
constexpr int FR_BAR = 229120 + 320;

__device__ __forceinline__ int rowaddr(int r) { return 32 * r + 16 * (r >> 2); }
struct hc { __half2 re, im; };
__device__ __forceinline__ hc bcast(cplx a) { hc r; r.re = __float2half2_rn(a.re); r.im = __float2half2_rn(a.im); return r; }
__device__ __forceinline__ hc hmul(hc v, hc s) {
  hc r;
  r.re = __hfma2(v.re, s.re, __hneg2(__hmul2(v.im, s.im)));
  r.im = __hfma2(v.re, s.im, __hmul2(v.im, s.re));
  return r;
}
__device__ __forceinline__ uint32_t h2u(__half2 h) { return *reinterpret_cast<uint32_t*>(&h); }
__device__ __forceinline__ void gen8(unsigned char* p, cplx s, cplx r1, hc r1sq, hc r2) {
  const cplx v1 = cmul(s, r1);
  hc p0; p0.re = __floats2half2_rn(s.re, v1.re); p0.im = __floats2half2_rn(s.im, v1.im);
  const hc p1 = hmul(p0, r1sq), p2 = hmul(p0, r2), p3 = hmul(p1, r2);
  *reinterpret_cast<uint4*>(p) = make_uint4(h2u(p0.re), h2u(p1.re), h2u(p2.re), h2u(p3.re));
  *reinterpret_cast<uint4*>(p + 8 * 112) = make_uint4(h2u(p0.im), h2u(p1.im), h2u(p2.im), h2u(p3.im));
}
__device__ __forceinline__ cplx csq(cplx a) { cplx r; r.re = a.re * a.re - a.im * a.im; r.im = 2.f * a.re * a.im; return r; }
__device__ __forceinline__ cplx cconj(cplx a) { a.im = -a.im; return a; }
__device__ __forceinline__ uint2 lds64(uint32_t a) { uint2 r; asm volatile("ld.shared.v2.u32 {%0,%1}, [%2];" : "=r"(r.x), "=r"(r.y) : "r"(a)); return r; }

__device__ __forceinline__ void front_phase(const bf16* __restrict__ Are, const bf16* __restrict__ Aim,
                                             const bf16* __restrict__ Bre, const bf16* __restrict__ Bim,
                                             const bf16* __restrict__ Cre, const bf16* __restrict__ Cim,
                                             const bf16* __restrict__ log_dt, const bf16* __restrict__ Dskip,
                                             const bf16* __restrict__ x, const bf16* __restrict__ wg,
                                             const bf16* __restrict__ wu, const bf16* __restrict__ wd,
                                             const CUtensorMap& tmU, const CUtensorMap& tmX) {
  extern __shared__ __align__(1024) unsigned char smem_all[];
  const int sub = threadIdx.x >> 7;
  const int tid = threadIdx.x & 127, lane = tid & 31;
  const int bar = 1 + sub;
  unsigned char* sm = smem_all + sub * SB_TOTAL;
  const uint32_t sbase = smem_u32(sm);
  const int w = ((tid >> 5) + sub) & 3;
  const int g = lane >> 2, t = lane & 3;
  const bool upper = threadIdx.x >= 256;
  const int hbar = upper ? 14 : 13;
  const bool do_ln = upper && blockIdx.x < 128;
  if (do_ln) ln1_load(x, blockIdx.x, smem_all + FR_LN);
  if (blockIdx.x >= 112) {
    if (do_ln) ln1_tile(blockIdx.x, smem_all + FR_LN);
    if (upper) named_bar(hbar, 256);
    const int t0 = (blockIdx.x - 112) + (upper ? 20 : 0);
    unsigned char* cs = smem_all + (upper ? 3 * CS_SMEM : 0);
#pragma unroll
    for (int i = 0; i < 3; i++)
      if (t0 + 40 * i < 112) colsum_load(wg, wu, t0 + 40 * i, cs + i * CS_SMEM);
    for (int i = (blockIdx.x - 112) * 512 + threadIdx.x; i < FF * DM * 2 / 128; i += 20 * 512)
      asm volatile("prefetch.global.L2 [%0];" ::"l"(reinterpret_cast<const char*>(wd) + (size_t)i * 128));
    cp_async_wait_all();
    named_bar(hbar, 256);
#pragma unroll
    for (int i = 0; i < 3; i++)
      if (t0 + 40 * i < 112) colsum_reduce(cs + i * CS_SMEM);
    named_bar(hbar, 256);
    const int wi = (threadIdx.x >> 5) & 7;
    if (wi < 3 && t0 + 40 * wi < 112) colsum_store(t0 + 40 * wi, cs + wi * CS_SMEM);
    named_bar(hbar, 256);
    if ((threadIdx.x & 255) == 0) {
      __threadfence();
      asm volatile("red.relaxed.gpu.global.add.u32 [%0], 1;" ::"l"(&g_cnt[8]) : "memory");
    }
    return;
  }
  const int d = blockIdx.x * 4 + sub;
  const int pidx = (d * NM + 64 * w) / 2 + lane;
  const uint32_t pAre = __ldg(reinterpret_cast<const uint32_t*>(Are) + pidx), pAim = __ldg(reinterpret_cast<const uint32_t*>(Aim) + pidx);
  const uint32_t pBre = __ldg(reinterpret_cast<const uint32_t*>(Bre) + pidx), pBim = __ldg(reinterpret_cast<const uint32_t*>(Bim) + pidx);
  const uint32_t pCre = __ldg(reinterpret_cast<const uint32_t*>(Cre) + pidx), pCim = __ldg(reinterpret_cast<const uint32_t*>(Cim) + pidx);
  const float dt = bf16r(expf(__bfloat162float(log_dt[d])));
  const uint32_t dsk2 = (uint32_t)__bfloat16_as_ushort(Dskip[d]) * 0x10001u;
  if (upper) ln1_tile(blockIdx.x, smem_all + FR_LN);
  if (tid < 90) *reinterpret_cast<uint4*>(sm + SB_U + tid * 16) = make_uint4(0, 0, 0, 0);
  if (tid >= 96 && tid < 105) *reinterpret_cast<uint4*>(sm + SB_U + 168 * 36 + (tid - 96) * 16) = make_uint4(0, 0, 0, 0);
  float w0re, w0im, w1re, w1im;
  {
    const float br0 = dt * bflo(pBre), bi0 = dt * bflo(pBim), br1 = dt * bfhi(pBre), bi1 = dt * bfhi(pBim);
    w0re = bflo(pCre) * br0 - bflo(pCim) * bi0; w0im = bflo(pCre) * bi0 + bflo(pCim) * br0;
    w1re = bfhi(pCre) * br1 - bfhi(pCim) * bi1; w1im = bfhi(pCre) * bi1 + bfhi(pCim) * br1;
  }
  float mx = fmaxf(fmaxf(fabsf(w0re), fabsf(w0im)), fmaxf(fabsf(w1re), fabsf(w1im)));
#pragma unroll
  for (int o = 16; o > 0; o >>= 1) mx = fmaxf(mx, __shfl_xor_sync(0xffffffffu, mx, o));
  int ex = (__float_as_uint(mx) >> 23) & 0xff;
  ex = min(max(ex, 1), 252);
  const float scale = __uint_as_float((uint32_t)(253 - ex) << 23);
  const float inv_scale = __uint_as_float((uint32_t)(ex + 1) << 23);

  float acc[5][4];
#pragma unroll
  for (int i = 0; i < 5; i++) { acc[i][0] = acc[i][1] = acc[i][2] = acc[i][3] = 0.f; }
  float k2048 = 0.f;
  unsigned char* tabw = sm + SB_TAB + w * SB_WREG;
  const uint32_t ldA = sbase + SB_TAB + w * SB_WREG + ((lane & 7) + 8 * ((lane >> 4) & 1)) * 112 + ((lane >> 3) & 1) * 16;
  const uint32_t ldB = sbase + SB_TAB + w * SB_WREG + ((lane & 7) + 8 * ((lane >> 3) & 1)) * 112 + 32 + (lane >> 4) * 16;
#pragma unroll 1
  for (int r = 0; r < 2; r++) {
    {
      const float a2 = dt * (r ? bfhi(pAre) : bflo(pAre)) * 1.4426950408889634f;
      const float bt = dt * (r ? bfhi(pAim) : bflo(pAim)) * 0.15915494309189535f;
      cplx W; W.re = (r ? w1re : w0re) * scale; W.im = -(r ? w1im : w0im) * scale;
      unsigned char* rec = tabw + ((lane >> 3) * 16 + (lane & 7)) * 112;
      const cplx y1 = zpow_acc(a2, -bt, 1.f), z8 = zpow_acc(a2, bt, 8.f), y128 = zpow_acc(a2, -bt, 128.f);
      const cplx y512 = zpow_acc(a2, -bt, 512.f), y1024 = zpow_acc(a2, -bt, 1024.f);
      const cplx z16 = csq(z8), z32 = csq(z16), z64 = csq(z32);
      const cplx y2 = csq(y1), y4 = csq(y2), y256 = csq(y128);
      cplx one; one.re = 1.f; one.im = 0.f;
      const hc h16 = bcast(z16), h32 = bcast(z32), h2 = bcast(y2), h4 = bcast(y4);
      const hc h128 = bcast(y128), h256 = bcast(y256), h512 = bcast(y512);
      gen8(rec, one, z8, h16, h32);
      gen8(rec + 16, z64, z8, h16, h32);
      gen8(rec + 32, W, y1, h2, h4);
      gen8(rec + 48, cmul(W, y128), y1, h2, h4);
      gen8(rec + 64, cmul(W, y256), y2, h4, h128);
      gen8(rec + 80, cmul(W, y512), y128, h256, h4);
      const cplx w1024 = cmul(W, y1024);
      gen8(rec + 96, w1024, y128, h256, h512);
      k2048 += w1024.re * y1024.re - w1024.im * y1024.im;
    }
    __syncwarp();
#pragma unroll
    for (int ks = 0; ks < 4; ks++) {
      uint32_t a0, a1, a2, a3, b0, b1, b2, b3;
      ldsm_x4_t(ldA + ks * 1792, a0, a1, a2, a3);
      ldsm_x4_t(ldB + ks * 1792, b0, b1, b2, b3);
      mma_f16(acc[0], a0, a1, a2, a3, b0, b1);
      mma_f16(acc[1], a0, a1, a2, a3, b2, b3);
      ldsm_x4_t(ldB + ks * 1792 + 32, b0, b1, b2, b3);
      mma_f16(acc[2], a0, a1, a2, a3, b0, b1);
      mma_f16(acc[3], a0, a1, a2, a3, b2, b3);
      ldsm_x2_t(ldB + ks * 1792 + 64, b0, b1);
      mma_f16(acc[4], a0, a1, a2, a3, b0, b1);
    }
    __syncwarp();
  }
  {
    float* red = reinterpret_cast<float*>(tabw);
#pragma unroll
    for (int hr = 0; hr < 2; hr++) {
      const int row = g + 8 * hr;
      *reinterpret_cast<float2*>(red + 8 * row + 2 * t) = make_float2(acc[0][2 * hr] * inv_scale, acc[0][2 * hr + 1] * inv_scale);
      *reinterpret_cast<float2*>(red + 128 + 8 * row + 2 * t) = make_float2(acc[1][2 * hr] * inv_scale, acc[1][2 * hr + 1] * inv_scale);
      *reinterpret_cast<float2*>(red + 256 + 64 * (t >> 1) + 2 * (t & 1) + 4 * row) = make_float2(acc[2][2 * hr] * inv_scale, acc[2][2 * hr + 1] * inv_scale);
      red[384 + 64 * (t & 1) + (t >> 1) + 2 * row] = acc[3][2 * hr] * inv_scale;
      red[384 + 64 * (t & 1) + 32 + (t >> 1) + 2 * row] = acc[3][2 * hr + 1] * inv_scale;
      red[512 + 32 * t + row] = acc[4][2 * hr] * inv_scale;
      red[512 + 32 * t + 16 + row] = acc[4][2 * hr + 1] * inv_scale;
    }
#pragma unroll
    for (int o = 16; o > 0; o >>= 1) k2048 += __shfl_xor_sync(0xffffffffu, k2048, o);
    if (lane == 0) red[640] = k2048 * inv_scale;
  }
  const uint32_t ubar = smem_u32(smem_all) + FR_BAR + (upper ? 8 : 0);
  const int ustg = upper ? FR_LN : FR_CS;
  if ((threadIdx.x & 255) == 0) {
    mbar_init(ubar, 1);
    asm volatile("fence.mbarrier_init.release.cluster;" ::: "memory");
    flag_wait(&g_cnt[7], (__ldcg(&g_epoch) + 1u) * 128u);
    asm volatile("fence.proxy.async;" ::: "memory");
    mbar_expect(ubar, 16384);
    tma2d(smem_u32(smem_all) + ustg, &tmU, ubar, (blockIdx.x * 4 + (sub & 2)) * 16, 0);
    tma2d(smem_u32(smem_all) + FR_X + (upper ? 8192 : 0), &tmX, ubar, (blockIdx.x * 4 + (sub & 2)) * 16, 0);
  }
  __syncwarp();
  named_bar(bar, 128);
  float* Kv = reinterpret_cast<float*>(sm + SB_KV);
  {
    const float* r0 = reinterpret_cast<const float*>(sm + SB_TAB);
    constexpr int WS = SB_WREG / 4;
    const float4 a = *reinterpret_cast<const float4*>(r0 + 4 * tid), b = *reinterpret_cast<const float4*>(r0 + WS + 4 * tid);
    const float4 c = *reinterpret_cast<const float4*>(r0 + 2 * WS + 4 * tid), e = *reinterpret_cast<const float4*>(r0 + 3 * WS + 4 * tid);
    *reinterpret_cast<float4*>(Kv + 4 * tid) =
        make_float4((a.x + b.x) + (c.x + e.x), (a.y + b.y) + (c.y + e.y), (a.z + b.z) + (c.z + e.z), (a.w + b.w) + (c.w + e.w));
    const int i = 512 + tid;
    Kv[i] = (r0[i] + r0[WS + i]) + (r0[2 * WS + i] + r0[3 * WS + i]);
    if (tid == 0) Kv[640] = (r0[640] + r0[WS + 640]) + (r0[2 * WS + 640] + r0[3 * WS + 640]);
  }
  named_bar(bar, 128);
  {
    auto tap_idx = [](int j) { const int m = j >> 1; const int r = (j & 1) ? m + (m & 1) : m; return min(max(j < 256 ? j : 128 + r, 0), 640); };
    float kd[3][3], f3[3], f2[3];
#pragma unroll
    for (int it = 0; it < 3; it++) {
      const int j = 528 - 2 * (tid + 128 * it);
#pragma unroll
      for (int e = 0; e < 3; e++) kd[it][e] = Kv[tap_idx(j + 1 - e)];
    }
    const int fa = tid >= 48, xa = tid - 48 * fa, ja = 144 - 2 * xa;
    const int fb = tid >> 6, xb = tid & 63, jb = 160 - 2 * xb;
#pragma unroll
    for (int e = 0; e < 3; e++) {
      f3[e] = Kv[min(max(384 + fa + 2 * (ja + 1 - e), 0), 640)];
      f2[e] = Kv[min(256 + fb + 2 * (jb + 1 - e), 640)];
    }
    const float k512 = Kv[384];
    uint32_t* ee = reinterpret_cast<uint32_t*>(sm + SB_KD);
#pragma unroll
    for (int it = 0; it < 3; it++) {
      const int x = tid + 128 * it, j = 528 - 2 * x;
      const float k0 = (j >= -1 && j <= 508) ? kd[it][0] : 0.f;
      float k1 = (j >= 0 && j <= 510) ? kd[it][1] : 0.f;
      const float k2 = (j >= 1 && j <= 510) ? kd[it][2] : 0.f;
      if (j == 510) k1 -= k512;
      const uint32_t we = pack_bf16(k1, k2), wo = pack_bf16(k0, k1);
      if (x < 272) { ee[2 * x] = we; ee[560 + 2 * x] = wo; }
      if (x < 272 && x >= 4) { ee[2 * x - 7] = we; ee[560 + 2 * x - 7] = wo; }
    }
    {
      const int hi = 128 - fa;
      const float k0 = (ja + 1 >= 64 && ja + 1 <= hi) ? f3[0] : 0.f, k1 = (ja >= 64 && ja <= hi) ? f3[1] : 0.f;
      const float k2 = (ja - 1 >= 64 && ja - 1 <= hi) ? f3[2] : 0.f;
      const uint32_t we = pack_bf16(k1, k2), wo = pack_bf16(k0, k1);
      uint32_t* p = reinterpret_cast<uint32_t*>(sm + SB_F3) + fa * 224;
      if (tid < 96) { p[2 * xa] = we; p[112 + 2 * xa] = wo; }
      if (tid < 96 && xa < 44) { p[2 * xa + 9] = we; p[112 + 2 * xa + 9] = wo; }
    }
    {
      const float k0 = (jb + 1 >= 64 && jb + 1 <= 127) ? f2[0] : 0.f, k1 = (jb >= 64 && jb <= 127) ? f2[1] : 0.f;
      const float k2 = (jb - 1 >= 64 && jb - 1 <= 127) ? f2[2] : 0.f;
      const uint32_t we = pack_bf16(k1, k2), wo = pack_bf16(k0, k1);
      uint32_t* p = reinterpret_cast<uint32_t*>(sm + SB_F2) + fb * 288;
      p[2 * xb] = we; p[144 + 2 * xb] = wo;
      p[2 * xb + 17] = we; p[144 + 2 * xb + 17] = wo;
    }
  }
  const float k1024 = Kv[512];
  named_bar(hbar, 256);
  mbar_wait(ubar, 0);
#pragma unroll
  for (int k = 0; k < 2; k++) {
    const int c = tid + 128 * k;
    *reinterpret_cast<uint4*>(sm + SB_U + rowaddr((c >> 1) + UZ) + (c & 1) * 16) =
        *reinterpret_cast<const uint4*>(smem_all + ustg + (c >> 1) * 64 + (sub & 1) * 32 + (c & 1) * 16);
  }
  named_bar(hbar, 256);
  const int krow = (lane & 7) + 8 * ((lane >> 3) & 1);
  if (w < 2) {
    float acd[4][2][4];
#pragma unroll
    for (int c = 0; c < 4; c++)
#pragma unroll
      for (int i = 0; i < 2; i++)
#pragma unroll
        for (int e = 0; e < 4; e++) acd[c][i][e] = 0.f;
    const uint32_t aQ = sbase + SB_U + rowaddr(UZ + 64 * w + 4 * krow) + (lane >> 4) * 16;
    const uint32_t pb = sbase + ((g & 1) ? SB_KDO + ((529 - g) / 2 + t) * 8 : SB_KD + ((528 - g) / 2 + t) * 8);
    uint32_t Q[36][4];
#define QOFF(j) (32 * (j) + 16 * (((j) + 64) / 4 - 16))
#pragma unroll
    for (int n = 0; n < 5; n++) ldsm_x4(aQ + QOFF(3 - n), Q[n][0], Q[n][1], Q[n][2], Q[n][3]);
#pragma unroll
    for (int q = 0; q < 33; q++) {
      if (q + 5 < 36) ldsm_x4(aQ + QOFF(3 - (q + 5)), Q[q + 5][0], Q[q + 5][1], Q[q + 5][2], Q[q + 5][3]);
      const uint2 e0 = lds64(pb - 32 * (2 * q));
      const uint2 e1 = lds64(pb - 32 * (2 * q + 1));
#pragma unroll
      for (int c = 0; c < 4; c++) {
        mma_bf16(acd[c][0], Q[3 - c + q][0], Q[3 - c + q][1], Q[3 - c + q][2], Q[3 - c + q][3], e0.x, e0.y);
        mma_bf16(acd[c][1], Q[3 - c + q][0], Q[3 - c + q][1], Q[3 - c + q][2], Q[3 - c + q][3], e1.x, e1.y);
      }
    }
#undef QOFF
    const int yl = (64 * (16 * w + g) + 2 * t + 16 * (g & 1) + 8 * ((g >> 1) & 1)) * 4;
    unsigned char* yb = sm + SB_Y + 8192;
#pragma unroll
    for (int c = 0; c < 4; c++)
#pragma unroll
      for (int nu = 0; nu < 2; nu++)
#pragma unroll
        for (int hr = 0; hr < 2; hr++)
          *reinterpret_cast<float2*>(yb + ((yl ^ ((16 * c + 8 * (nu ^ (c >> 1))) * 4)) + hr * 2048)) = make_float2(acd[c][nu][2 * hr], acd[c][nu][2 * hr + 1]);
  } else {
    const int yl = (16 * (g ^ ((g >> 2) & 1)) + 2 * t + 8 * ((g >> 1) & 1)) * 4;
    if (w == 2) {
      float ac[7][2][4];
#pragma unroll
      for (int T = 0; T < 7; T++)
#pragma unroll
        for (int i = 0; i < 2; i++)
#pragma unroll
          for (int e = 0; e < 4; e++) ac[T][i][e] = 0.f;
      uint32_t BA[2][4];
#pragma unroll
      for (int ks = 0; ks < 2; ks++)
#pragma unroll
        for (int r = 0; r < 4; r++) {
          uint32_t v = 0;
#pragma unroll
          for (int e = 0; e < 2; e++) {
            const int dlt = (2 * t + e + 8 * (r >> 1) + 16 * ks - 8) - g;
            const bool on = (r & 1) ? (dlt >= -5 && dlt <= -3) : (dlt >= -2 && dlt <= 2);
            v |= on ? (0x3f80u << (16 * e)) : 0u;
          }
          BA[ks][r] = v;
        }
      const int chl = 2 * UZ + (lane & 7) + (lane >> 3) - 1;
      const uint32_t ub = sbase + SB_U + rowaddr(chl >> 1) + (chl & 1) * 16;
      const uint32_t fb = sbase + SB_F2 + (80 - (g - t)) * 8;
#pragma unroll
      for (int sp = 0; sp < 2; sp++) {
        uint32_t bb[2][7][2];
#pragma unroll
        for (int i = 0; i < 7 - sp; i++) {
          const int beta = 11 - sp - 2 * i;
#pragma unroll
          for (int o = 0; o < 2; o++) {
            uint32_t u0, u1, u2, u3;
            ldsm_x4(ub + (2 * beta + o) * 144, u0, u1, u2, u3);
            float z[4] = {0.f, 0.f, 0.f, 0.f};
            mma_bf16(z, BA[0][0], BA[0][1], BA[0][2], BA[0][3], u0, u1);
            mma_bf16(z, BA[1][0], BA[1][1], BA[1][2], BA[1][3], u2, u3);
            bb[0][i][o] = pack_bf16(z[0], z[1]);
            bb[1][i][o] = pack_bf16(z[2], z[3]);
          }
        }
#pragma unroll
        for (int f = 0; f < 2; f++) {
#pragma unroll
          for (int k = 0; k < 3; k++) {
#pragma unroll
            for (int nu = 0; nu < 2; nu++) {
              const uint2 A01 = lds64(fb + f * 1152 + nu * 576 - 32 * (6 + 2 * (2 * k + sp)));
              const uint2 A23 = lds64(fb + f * 1152 + nu * 576 - 32 * (5 + 2 * (2 * k + sp)));
#pragma unroll
              for (int i = 0; i < 7 - sp; i++) {
                const int T = 7 - i + k;
                if (T <= 7) mma_bf16(ac[T - 1][nu], A01.x, A01.y, A23.x, A23.y, bb[f][i][0], bb[f][i][1]);
              }
            }
          }
        }
      }
      named_bar(5 + bar, 96);
      unsigned char* yb = sm + SB_Y;
#pragma unroll
      for (int T = 0; T <= 7; T++)
#pragma unroll
        for (int nu = 0; nu < 2; nu++)
#pragma unroll
          for (int hr = 0; hr < 2; hr++)
            *reinterpret_cast<float2*>(yb + ((yl ^ ((8 * (nu ^ hr)) * 4)) + (16 * T + 8 * hr) * 64)) =
                T ? make_float2(ac[T ? T - 1 : 0][nu][2 * hr], ac[T ? T - 1 : 0][nu][2 * hr + 1]) : make_float2(0.f, 0.f);
    } else {
      float ac[5][2][4];
#pragma unroll
      for (int T = 0; T < 5; T++)
#pragma unroll
        for (int i = 0; i < 2; i++)
#pragma unroll
          for (int e = 0; e < 4; e++) ac[T][i][e] = 0.f;
      const uint32_t fb = sbase + SB_F3 + ((g & 1) ? 448 + ((145 - g) / 2 + t) * 8 : ((144 - g) / 2 + t) * 8);
      uint32_t ur[3];
#pragma unroll
      for (int sg = 0; sg < 3; sg++) ur[sg] = sbase + SB_U + rowaddr(UZ + (lane & 7) + 8 * (lane >> 4) + sg - 1) + ((lane >> 3) & 1) * 16;
#pragma unroll 1
      for (int f = 0; f < 2; f++) {
        uint32_t BA[3][4];
        const int lo = f ? -11 : -4, hi = f ? -5 : 4;
#pragma unroll
        for (int sg = 0; sg < 3; sg++)
#pragma unroll
          for (int r = 0; r < 4; r++) {
            uint32_t v = 0;
#pragma unroll
            for (int e = 0; e < 2; e++) {
              const int dlt = (2 * t + e + 8 * (r >> 1) + 16 * (sg - 1)) - (g + 8 * (r & 1));
              v |= (dlt >= lo && dlt <= hi) ? (0x3f80u << (16 * e)) : 0u;
            }
            BA[sg][r] = v;
          }
        uint2 A01[5], A23[5];
#pragma unroll
        for (int s = 0; s < 5; s++) {
          A01[s] = lds64(fb + f * 896 - 32 * (8 + 2 * s));
          A23[s] = lds64(fb + f * 896 - 32 * (7 + 2 * s));
        }
#pragma unroll
        for (int beta = 3; beta >= -1; beta--) {
          float z0[4] = {0.f, 0.f, 0.f, 0.f}, z1[4] = {0.f, 0.f, 0.f, 0.f};
#pragma unroll
          for (int sg = 0; sg < 3; sg++) {
            uint32_t u0, u1, u2, u3;
            ldsm_x4(ur[sg] + beta * 576, u0, u1, u2, u3);
            mma_bf16(z0, BA[sg][0], BA[sg][1], BA[sg][2], BA[sg][3], u0, u1);
            mma_bf16(z1, BA[sg][0], BA[sg][1], BA[sg][2], BA[sg][3], u2, u3);
          }
          const uint32_t b0 = pack_bf16(z0[0], z0[1]), b1 = pack_bf16(z1[0], z1[1]);
          const uint32_t b2 = pack_bf16(z0[2], z0[3]), b3 = pack_bf16(z1[2], z1[3]);
#pragma unroll
          for (int s = 0; s < 5; s++) {
            const int T = beta + 4 + s;
            if (T <= 7) {
              mma_bf16(ac[T - 3][0], A01[s].x, A01[s].y, A23[s].x, A23[s].y, b0, b1);
              mma_bf16(ac[T - 3][1], A01[s].x, A01[s].y, A23[s].x, A23[s].y, b2, b3);
            }
          }
        }
      }
      {
        const uint32_t nk = (uint32_t)__bfloat16_as_ushort(__float2bfloat16_rn(-k1024));
        uint32_t PC[5];
#pragma unroll
        for (int m = 0; m < 5; m++) {
          const int j = 8 * (125 + m) + g - 2 * t;
          PC[m] = ((j == 1020 || j == 1021) ? nk : 0u) | ((j == 1021 || j == 1022) ? (nk << 16) : 0u);
        }
#pragma unroll
        for (int k = 0; k < 2; k++) {
          const uint32_t ab = sbase + SB_U + rowaddr(UZ + 48 - 63 - k + krow) + (lane >> 4) * 16;
#pragma unroll
          for (int T = 3; T <= 7; T++) {
            uint32_t a0, a1, a2, a3;
            ldsm_x4(ab + (T - 3) * 576, a0, a1, a2, a3);
            mma_bf16(ac[T - 3][0], a0, a1, a2, a3, PC[1 + 2 * k], PC[2 * k]);
            mma_bf16(ac[T - 3][1], a0, a1, a2, a3, PC[2 + 2 * k], PC[1 + 2 * k]);
          }
        }
      }
      unsigned char* yb = sm + SB_Y + 16384;
#pragma unroll
      for (int T = 0; T <= 7; T++)
#pragma unroll
        for (int nu = 0; nu < 2; nu++)
#pragma unroll
          for (int hr = 0; hr < 2; hr++)
            *reinterpret_cast<float2*>(yb + ((yl ^ ((8 * (nu ^ hr)) * 4)) + (16 * T + 8 * hr) * 64)) =
                T >= 3 ? make_float2(ac[T >= 3 ? T - 3 : 0][nu][2 * hr], ac[T >= 3 ? T - 3 : 0][nu][2 * hr + 1]) : make_float2(0.f, 0.f);
    }
  }
  if (w < 2) asm volatile("bar.arrive %0, 96;" ::"r"(5 + bar) : "memory");
  named_bar(bar, 128);
  {
    const __nv_bfloat162 ds = *reinterpret_cast<const __nv_bfloat162*>(&dsk2);
    const int r0 = tid >> 2, ch = tid & 3;
    const int yo = (16 * (r0 ^ ((r0 >> 2) & 1)) + ((4 * ch) ^ (8 * (((r0 >> 1) ^ (r0 >> 3)) & 1)))) * 4;
    const int uo = SB_U + rowaddr(r0 + UZ) + ch * 8;
#pragma unroll
    for (int k = 0; k < 4; k++) {
      const float4 a = *reinterpret_cast<const float4*>(sm + SB_Y + yo + k * 2048);
      const float4 b = *reinterpret_cast<const float4*>(sm + SB_Y + 8192 + yo + k * 2048);
      const float4 c = *reinterpret_cast<const float4*>(sm + SB_Y + 16384 + yo + k * 2048);
      const uint2 uw = *reinterpret_cast<const uint2*>(sm + uo + k * 1152);
      const uint2 xw = *reinterpret_cast<const uint2*>(smem_all + FR_X + (sub >> 1) * 8192 + r0 * 64 + (sub & 1) * 32 + ch * 8 + k * 2048);
      const uint32_t y0 = pack_bf16(b.x + (a.x + c.x), b.y + (a.y + c.y)), y1 = pack_bf16(b.z + (a.z + c.z), b.w + (a.w + c.w));
      const __nv_bfloat162 h0 = __hadd2_rn(*reinterpret_cast<const __nv_bfloat162*>(&xw.x),
          __hadd2_rn(*reinterpret_cast<const __nv_bfloat162*>(&y0), __hmul2_rn(*reinterpret_cast<const __nv_bfloat162*>(&uw.x), ds)));
      const __nv_bfloat162 h1 = __hadd2_rn(*reinterpret_cast<const __nv_bfloat162*>(&xw.y),
          __hadd2_rn(*reinterpret_cast<const __nv_bfloat162*>(&y1), __hmul2_rn(*reinterpret_cast<const __nv_bfloat162*>(&uw.y), ds)));
      *reinterpret_cast<uint2*>(g_hT + (size_t)d * SEQ + tid * 4 + k * 512) =
          make_uint2(*reinterpret_cast<const uint32_t*>(&h0), *reinterpret_cast<const uint32_t*>(&h1));
    }
  }
  if (threadIdx.x < 480) {
    asm volatile("bar.arrive 11, 512;" ::: "memory");
  } else {
    fence_async();
    asm volatile("bar.arrive 15, 512;" ::: "memory");
    named_bar(11, 512);
    if (lane == 0) {
      __threadfence();
      asm volatile("red.relaxed.gpu.global.add.u32 [%0], 1;" ::"l"(&g_cnt[blockIdx.x >> 4]) : "memory");
    }
    __syncwarp();
  }
}

constexpr int M_A     = 0;
constexpr int M_W     = 7 * 16384;
constexpr int M_XB    = M_W + 3 * 32768;
constexpr int M_CS    = M_XB + 14336;
constexpr int M_BAR   = M_CS + 1792;
constexpr int M_TOTAL = M_BAR + 384;

__device__ __forceinline__ float sigmoid_fast(float x) {
  float th; asm("tanh.approx.f32 %0, %1;" : "=f"(th) : "f"(0.5f * x));
  return fmaf(0.5f, th, 0.5f);
}
template <int NCB, int NA, int OFS>
__device__ __forceinline__ void g1_pack(const float (&acc)[NA], uint32_t* pk, const float* cs,
                                        float mb0, float rs0, float mb1, float rs1, int lane) {
  const int t = lane & 3;
  const float c0 = -mb0 * rs0, c1 = -mb1 * rs1;
#pragma unroll
  for (int cb = 0; cb < NCB; cb++) {
    const float2 sc = *reinterpret_cast<const float2*>(cs + cb * 8 + 2 * t);
    pk[2 * cb]     = pack_bf16(fmaf(acc[OFS + 4 * cb + 0], rs0, c0 * sc.x), fmaf(acc[OFS + 4 * cb + 1], rs0, c0 * sc.y));
    pk[2 * cb + 1] = pack_bf16(fmaf(acc[OFS + 4 * cb + 2], rs1, c1 * sc.x), fmaf(acc[OFS + 4 * cb + 3], rs1, c1 * sc.y));
  }
}
__device__ __forceinline__ uint32_t glu2(uint32_t gw, uint32_t uw) {
  return pack_bf16(sigmoid_fast(bflo(gw)) * bflo(uw), sigmoid_fast(bfhi(gw)) * bfhi(uw));
}
__device__ __forceinline__ uint32_t w2_slot(int j, int kp) {
  const int sl = j % 10;
  if (sl < 6) return M_W + ((sl >> 1) + 2) % 3 * 32768 + (sl & 1) * 16384;
  const int i = sl - 6;
  return M_A + (i + (i >= kp ? 3 : 0)) * 16384;
}

__global__ void __cluster_dims__(2, 1, 1) __launch_bounds__(512, 1)
k_all(const bf16* __restrict__ Are, const bf16* __restrict__ Aim, const bf16* __restrict__ Bre, const bf16* __restrict__ Bim,
      const bf16* __restrict__ Cre, const bf16* __restrict__ Cim, const bf16* __restrict__ log_dt, const bf16* __restrict__ Dskip,
      const bf16* __restrict__ x, const bf16* __restrict__ wgp, const bf16* __restrict__ wup, const bf16* __restrict__ wdp,
      const __grid_constant__ CUtensorMap tmLu, const __grid_constant__ CUtensorMap tmLx,
      const __grid_constant__ CUtensorMap tmA, const __grid_constant__ CUtensorMap tmG,
      const __grid_constant__ CUtensorMap tmU, const __grid_constant__ CUtensorMap tmD, bf16* __restrict__ out) {
  extern __shared__ __align__(1024) unsigned char smem[];
  const uint32_t sb = smem_u32(smem);
  const int tid = threadIdx.x, lane = tid & 31, warp = tid >> 5;
  const uint32_t barA = sb + M_BAR, barF = barA + 56, barE = barF + 24, barS = barE + 24;
  const uint32_t barW2 = barS + 8, barAf = barW2 + 112, barX = barAf + 8, barH = barX + 8, barE2 = barH + 16;
  if (lane == 0 && warp >= 8 && warp < 13) {
#pragma unroll
    for (int i = 0; i < 8; i++) {
      const int b = (warp - 8) * 8 + i;
      if (b < 36) mbar_init(barA + 8 * b, ((b >= 10 && b < 13) || b == 28 || b >= 32) ? 2 : (b == 29 ? 4 : 1));
    }
    asm volatile("fence.mbarrier_init.release.cluster;" ::: "memory");
    if (sb & 1023) __trap();
  }
  if (tid >= 480 && tid < 484) prefetch_tm(tid == 480 ? &tmG : tid == 481 ? &tmU : tid == 482 ? &tmA : &tmD);
  __syncwarp();

  front_phase(Are, Aim, Bre, Bim, Cre, Cim, log_dt, Dskip, x, wgp, wup, wdp, tmLu, tmLx);

  fence_async();
  if (warp < 15 || blockIdx.x >= 112) named_bar(15, 512);
  const uint32_t rank = blockIdx.x & 1;
  const bool live = blockIdx.x < 128;
  const int pr = live ? blockIdx.x >> 1 : 0;
  const int mt = pr & 15;
  const int fp = pr >> 4;
  const int fj = 4 * rank + fp;
  const int kp = min((112 * fp) >> 6, 4);
  cluster_arrive();

  if (warp >= 8) {
    const unsigned int ep = __ldcg(&g_epoch);
    asm volatile("setmaxnreg.dec.sync.aligned.u32 24;");
    if (!live || warp >= 12) {
      cluster_wait();
      if (warp == 9) { named_bar(2, 288); named_bar(3, 288); }
    } else if (warp == 8) {
      if (lane == 0) {
        for (int it = 0; it < 14; it++) {
          const int s = it % 3, rnd = it / 3;
          const bool pb = it >= 7;
          const int kb = pb ? it - 7 : it;
          if (rnd > 0) mbar_wait(barE + 8 * s, (rnd - 1) & 1);
          mbar_expect(barF + 8 * s, 32768);
          const uint32_t dst = sb + M_W + s * 32768;
          const int c0 = 224 * fj + (pb ? 128 : 0);
          tma2d(dst, &tmG, barF + 8 * s, c0, 64 * kb);
          tma2d(dst + 16384, &tmU, barF + 8 * s, c0, 64 * kb);
          tma2d(dst + 8192, &tmG, barF + 8 * s, c0 + 64, 64 * kb);
          tma2d(dst + 24576, &tmU, barF + 8 * s, c0 + 64, 64 * kb);
        }
        for (int j = 0; j < 14; j++) {
          if (j < 6 && !(j & 1)) { const int it = 11 + (j >> 1); mbar_wait(barE + 8 * (it % 3), (it / 3) & 1); }
          if (j == 6) mbar_wait(barAf, 0);
          if (j >= 10) mbar_wait(barE2 + 8 * (j - 10), 0);
          mbar_expect(barW2 + 8 * j, 16384);
          const uint32_t dst = sb + w2_slot(j, kp);
#pragma unroll
          for (int h = 0; h < 2; h++) {
            const int u = 2 * j + h;
            int c, o;
            if (u < 7) { c = 0; o = u; } else if (u < 19) { c = 1 + (u - 7) / 4; o = (u - 7) % 4; } else { c = 1 + (u - 19) / 3; o = 4 + (u - 19) % 3; }
            const int row = (4 * rank + ((fp + c) & 3)) * 224 + 32 * o;
            tma2d(dst + h * 4096, &tmD, barW2 + 8 * j, 112 * fp, row);
            tma2d(dst + 8192 + h * 4096, &tmD, barW2 + 8 * j, 112 * fp + 64, row);
          }
        }
      }
      __syncwarp();
      cluster_wait();
    } else if (warp == 9) {
      if (lane < 7) flag_wait(&g_cnt[lane], (ep + 1u) * 16u);
      cluster_wait();
      if (lane == 0) {
        asm volatile("fence.proxy.async;" ::: "memory");
        for (int k = 0; k < 7; k++) {
          mbar_expect(barA + 8 * k, 16384);
          tma3d_mc(sb + M_A + k * 16384 + rank * 8192, &tmA, barA + 8 * k, 0, 64 * k, 2 * mt + rank, (uint16_t)3);
        }
      }
      __syncwarp();
#pragma unroll 1
      for (int p = 0; p < 2; p++) {
        named_bar(2 + p, 288);
        if (lane == 0) {
          asm volatile("fence.acq_rel.gpu;" ::: "memory");
          asm volatile("red.relaxed.gpu.global.add.u32 [%0], 1;" ::"l"(&g_cnt2[(mt * 2 + rank) * 2 + p]) : "memory");
        }
        __syncwarp();
      }
    } else if (warp == 10) {
      cluster_wait();
      if (lane == 0) {
#pragma unroll 1
        for (int p = 0; p < 2; p++) {
          flag_wait(&g_cnt2[(mt * 2 + rank) * 2 + p], (ep + 1u) * 4u);
          mbar_arrive(barH + 8 * p);
        }
      }
    } else {
      if (lane == 0) flag_wait(&g_cnt[8], (ep + 1u) * 40u);
      __syncwarp();
      float* cs = reinterpret_cast<float*>(smem + M_CS);
      for (int i = lane; i < 448; i += 32) cs[i] = __ldcg(&g_cs[(i >= 224 ? FF + i - 224 : i) + fj * 224]);
      __syncwarp();
      if (lane == 0) mbar_arrive(barS);
      cluster_wait();
    }
    __syncwarp();
    cluster_arrive(); cluster_wait();
  } else {
    asm volatile("setmaxnreg.inc.sync.aligned.u32 232;");
    const int wg = warp >> 2, wq = warp & 3;
    const bool elect = (tid & 127) == 0;
    const float* cs = reinterpret_cast<const float*>(smem + M_CS);
#define RELEASE(b) do { if (elect) mbar_arrive(b); } while (0)
#define PUBLISH(p) asm volatile("bar.arrive %0, 288;" ::"r"(2 + (p)) : "memory")
    const int dr = (lane & 7) + 8 * (lane >> 4), tc = 2 * wq + ((lane >> 3) & 1);
    const uint32_t aT = sb + M_A + wg * 8192 + dr * 128 + ((tc ^ (lane & 7)) << 4);
    uint4* hbase = reinterpret_cast<uint4*>(g_P) + (size_t)(mt * 8 * 8 + warp) * (14 * 32) + lane;
    const uint32_t dead = live ? 0u : 1u;
    float mb0, rs0, mb1, rs1;
    uint32_t pkA[64];
    {
      float accA[64], accB[64];
      float s0 = 0.f, q0 = 0.f, s1 = 0.f, q1 = 0.f;
#pragma unroll
      for (int kb = 0; kb < 7; kb++) {
        const int s = kb % 3;
        mbar_wait(barA + 8 * kb, (0) | dead);
        uint32_t af[4][4];
#pragma unroll
        for (int k = 0; k < 4; k++) ldsm_x4_t(aT + kb * 16384 + k * 2048, af[k][0], af[k][1], af[k][2], af[k][3]);
        mbar_wait(barF + 8 * s, ((kb / 3) & 1) | dead);
        const uint64_t db = mk_desc(sb + M_W + s * 32768, 8192, 1024, 1);
        wg_fence();
#pragma unroll
        for (int k = 0; k < 4; k++) {
          wgmma_rs_n128(accA, af[k][0], af[k][1], af[k][2], af[k][3], db + k * 128, (kb | k) != 0);
          wgmma_rs_n128(accB, af[k][0], af[k][1], af[k][2], af[k][3], db + 1024 + k * 128, (kb | k) != 0);
        }
        wg_commit();
        if (kb > 0) { wg_wait<1>(); RELEASE(barE + 8 * ((kb - 1) % 3)); }
#pragma unroll
        for (int k = 0; k < 4; k++) {
#pragma unroll
          for (int h = 0; h < 2; h++) {
            const float a = bflo(af[k][2 * h]), b = bfhi(af[k][2 * h]), c = bflo(af[k][2 * h + 1]), e = bfhi(af[k][2 * h + 1]);
            s0 += a + b; q0 = fmaf(a, a, fmaf(b, b, q0));
            s1 += c + e; q1 = fmaf(c, c, fmaf(e, e, q1));
          }
        }
      }
#pragma unroll
      for (int o = 1; o <= 2; o <<= 1) {
        s0 += __shfl_xor_sync(0xffffffffu, s0, o); q0 += __shfl_xor_sync(0xffffffffu, q0, o);
        s1 += __shfl_xor_sync(0xffffffffu, s1, o); q1 += __shfl_xor_sync(0xffffffffu, q1, o);
      }
      s0 *= (1.0f / DM); s1 *= (1.0f / DM);
      mb0 = bf16r(s0); mb1 = bf16r(s1);
      rs0 = __fdiv_rn(1.0f, bf16r(sqrtf(bf16r(bf16r(fmaxf(q0 * (1.0f / DM) - s0 * s0, 0.f)) + 1e-5f))));
      rs1 = __fdiv_rn(1.0f, bf16r(sqrtf(bf16r(bf16r(fmaxf(q1 * (1.0f / DM) - s1 * s1, 0.f)) + 1e-5f))));
      mbar_wait(barS, (0) | dead);
      wg_wait<0>();
      RELEASE(barE + 0);
      g1_pack<16, 64, 0>(accA, pkA, cs, mb0, rs0, mb1, rs1, lane);
      g1_pack<16, 64, 0>(accB, pkA + 32, cs + 224, mb0, rs0, mb1, rs1, lane);
    }
    uint32_t hf[56];
    uint32_t pkB[48];
    uint4* hown = live ? hbase + (size_t)fj * (8 * 14 * 32) : reinterpret_cast<uint4*>(g_dummy) + lane;
    {
      float accG[48], accU[48];
#pragma unroll
      for (int kb = 0; kb < 7; kb++) {
        const int it = kb + 7, s = it % 3;
        uint32_t af[4][4];
#pragma unroll
        for (int k = 0; k < 4; k++) ldsm_x4_t(aT + kb * 16384 + k * 2048, af[k][0], af[k][1], af[k][2], af[k][3]);
        mbar_wait(barF + 8 * s, ((it / 3) & 1) | dead);
        const uint64_t db = mk_desc(sb + M_W + s * 32768, 8192, 1024, 1);
        wg_fence();
#pragma unroll
        for (int k = 0; k < 4; k++) {
          wgmma_rs_n96(accG, af[k][0], af[k][1], af[k][2], af[k][3], db + k * 128, (kb | k) != 0);
          wgmma_rs_n96(accU, af[k][0], af[k][1], af[k][2], af[k][3], db + 1024 + k * 128, (kb | k) != 0);
        }
        wg_commit();
        if (kb > 0) { wg_wait<1>(); RELEASE(barE + 8 * ((it - 1) % 3)); }
        if (kb < 4) {
#pragma unroll
          for (int i = 0; i < 8; i++) hf[8 * kb + i] = glu2(pkA[8 * kb + i], pkA[32 + 8 * kb + i]);
          hown[(2 * kb) * 32] = make_uint4(hf[8 * kb], hf[8 * kb + 1], hf[8 * kb + 2], hf[8 * kb + 3]);
          hown[(2 * kb + 1) * 32] = make_uint4(hf[8 * kb + 4], hf[8 * kb + 5], hf[8 * kb + 6], hf[8 * kb + 7]);
          if (kb == 3) PUBLISH(0);
        }
      }
      wg_wait<0>();
      if (elect) { mbar_arrive(barE + 8 * (13 % 3)); mbar_arrive(barAf); }
      g1_pack<12, 48, 0>(accG, pkB, cs + 128, mb0, rs0, mb1, rs1, lane);
      g1_pack<12, 48, 0>(accU, pkB + 24, cs + 352, mb0, rs0, mb1, rs1, lane);
    }
#pragma unroll
    for (int i = 0; i < 24; i++) hf[32 + i] = glu2(pkB[i], pkB[24 + i]);
#pragma unroll
    for (int q = 0; q < 6; q++) hown[(8 + q) * 32] = make_uint4(hf[32 + 4 * q], hf[33 + 4 * q], hf[34 + 4 * q], hf[35 + 4 * q]);
    PUBLISH(1);
    float acc[56];
    auto hsrc = [&](int i) -> const uint4* {
      int c, o;
      if (i < 38) { c = 1 + (i - 14) / 8; o = (i - 14) % 8; } else { c = 1 + (i - 38) / 6; o = 8 + (i - 38) % 6; }
      return hbase + (size_t)(4 * rank + ((fp + c) & 3)) * (8 * 14 * 32) + o * 32;
    };
    uint4 hq[4][4];
#pragma unroll
    for (int j = 0; j < 14; j++) {
      if (j == 1) mbar_wait(barH, dead);
      if (j == 7) mbar_wait(barH + 8, dead);
#pragma unroll
      for (int k = 0; k < 4; k++) {
        const int i = 4 * (j + 2) + k;
        if (i >= 14 && i < 56) hq[(j + 2) & 3][k] = __ldcg(hsrc(i));
      }
      mbar_wait(barW2 + 8 * j, (0) | dead);
      const uint64_t db = mk_desc(sb + w2_slot(j, kp), 8192, 1024, 1);
      wg_fence();
#pragma unroll
      for (int k = 0; k < 4; k++) {
        const int i = 4 * j + k;
        if (i < 14) wgmma_rs_n112(acc, hf[4 * i], hf[4 * i + 1], hf[4 * i + 2], hf[4 * i + 3], db + k * 128, i != 0);
        else wgmma_rs_n112(acc, hq[j & 3][k].x, hq[j & 3][k].y, hq[j & 3][k].z, hq[j & 3][k].w, db + k * 128, 1);
      }
      wg_commit();
      if (j > 0) { wg_wait<1>(); if (j <= 4) RELEASE(barE2 + 8 * (j - 1)); }
    }
    wg_wait<0>();
    cluster_wait();
    if (wg != (int)rank) {
      asm volatile("bar.arrive 1, 256;" ::: "memory");
      const uint32_t xd = mapa(sb + M_XB, rank ^ 1) + (tid & 127) * 16;
#pragma unroll
      for (int q = 0; q < 7; q++)
        asm volatile("st.shared::cluster.v4.b32 [%0], {%1,%2,%3,%4};" ::"r"(xd + q * 2048), "r"(pack_bf16(acc[8 * q], acc[8 * q + 1])),
                     "r"(pack_bf16(acc[8 * q + 2], acc[8 * q + 3])), "r"(pack_bf16(acc[8 * q + 4], acc[8 * q + 5])),
                     "r"(pack_bf16(acc[8 * q + 6], acc[8 * q + 7])) : "memory");
      __syncwarp();
      if (lane == 0) asm volatile("mbarrier.arrive.release.cluster.shared::cluster.b64 _, [%0];" ::"r"(mapa(barX, rank ^ 1)) : "memory");
    } else {
      uint32_t hr[7][4];
      const int d0 = 112 * fp;
#pragma unroll
      for (int q = 0; q < 7; q++) {
        const int dd = d0 + 16 * q;
        ldsm_x4_t(aT + (dd >> 6) * 16384 + (dd & 63) * 128, hr[q][0], hr[q][1], hr[q][2], hr[q][3]);
      }
      { uint32_t ok; int it = 0;
        do { asm volatile("{.reg .pred p; mbarrier.try_wait.parity.acquire.cluster.shared::cta.b64 p, [%1], 0; selp.u32 %0,1,0,p;}"
                          : "=r"(ok) : "r"(barX) : "memory"); } while (!ok && ++it < (1 << 24)); }
      const uint32_t stg = sb + M_W + wq * 3840;
      const uint32_t so = stg + ((lane & 7) + 8 * ((lane >> 3) & 1)) * 240 + (lane >> 4) * 16;
      named_bar(1, 256);
#pragma unroll
      for (int q = 0; q < 7; q++) {
        const uint4 v = *reinterpret_cast<const uint4*>(smem + M_XB + q * 2048 + (tid & 127) * 16);
        const uint32_t m0 = pack_bf16(acc[8 * q] + bflo(v.x), acc[8 * q + 1] + bfhi(v.x)), m1 = pack_bf16(acc[8 * q + 2] + bflo(v.y), acc[8 * q + 3] + bfhi(v.y));
        const uint32_t m2 = pack_bf16(acc[8 * q + 4] + bflo(v.z), acc[8 * q + 5] + bfhi(v.z)), m3 = pack_bf16(acc[8 * q + 6] + bflo(v.w), acc[8 * q + 7] + bfhi(v.w));
        stsm_x4(so + q * 32, pack_bf16(bflo(hr[q][0]) + bflo(m0), bfhi(hr[q][0]) + bfhi(m0)), pack_bf16(bflo(hr[q][1]) + bflo(m1), bfhi(hr[q][1]) + bfhi(m1)),
                pack_bf16(bflo(hr[q][2]) + bflo(m2), bfhi(hr[q][2]) + bfhi(m2)), pack_bf16(bflo(hr[q][3]) + bflo(m3), bfhi(hr[q][3]) + bfhi(m3)));
      }
      __syncwarp();
      bf16* o = live ? out + (size_t)(mt * 128 + 64 * wg + 16 * wq) * DM + d0 : g_dummy;
#pragma unroll
      for (int k = 0; k < 7; k++) {
        const int c = lane + 32 * k;
        const int r = c / 14, ch = c - 14 * r;
        *reinterpret_cast<uint4*>(o + (size_t)r * DM + ch * 8) = *reinterpret_cast<const uint4*>(smem + M_W + wq * 3840 + r * 240 + ch * 16);
      }
    }
    if (tid == 0 && live) {
      const unsigned int n = atomicAdd(&g_done, 1u);
      if ((n & 127u) == 127u) atomicAdd(&g_epoch, 1u);
    }
    __syncwarp();
    cluster_arrive(); cluster_wait();
#undef PUBLISH
#undef RELEASE
  }
}

typedef CUresult (*EncFn)(CUtensorMap*, CUtensorMapDataType, cuuint32_t, void*, const cuuint64_t*, const cuuint64_t*,
                          const cuuint32_t*, const cuuint32_t*, CUtensorMapInterleave, CUtensorMapSwizzle,
                          CUtensorMapL2promotion, CUtensorMapFloatOOBfill);

static void make_map(EncFn enc, CUtensorMap* tm, const void* ptr, int rank, const uint64_t* dims, const uint64_t* strides_bytes,
                     const uint32_t* box, CUtensorMapSwizzle swz) {
  cuuint64_t gd[3], gs[2]; cuuint32_t bd[3], es[3] = {1, 1, 1};
  for (int i = 0; i < rank; i++) { gd[i] = dims[i]; bd[i] = box[i]; }
  for (int i = 0; i < rank - 1; i++) gs[i] = strides_bytes[i];
  enc(tm, CU_TENSOR_MAP_DATA_TYPE_BFLOAT16, rank, const_cast<void*>(ptr), gd, gs, bd, es, CU_TENSOR_MAP_INTERLEAVE_NONE, swz,
      CU_TENSOR_MAP_L2_PROMOTION_L2_128B, CU_TENSOR_MAP_FLOAT_OOB_FILL_NONE);
}

template <class K, class... Args>
static void launch_k(K kern, int grid, int block, int smem, bool pdl, Args... args) {
  cudaLaunchConfig_t cfg = {};
  cfg.gridDim = dim3(grid); cfg.blockDim = dim3(block); cfg.dynamicSmemBytes = smem; cfg.stream = cudaStreamPerThread;
  cudaLaunchAttribute at[1];
  at[0].id = cudaLaunchAttributeProgrammaticStreamSerialization;
  at[0].val.programmaticStreamSerializationAllowed = 1;
  cfg.attrs = at; cfg.numAttrs = pdl ? 1 : 0;
  cudaLaunchKernelEx(&cfg, kern, args...);
}

extern "C" void kernel_launch(void* const* d_in, const int* in_sizes, int n_in, void* d_out, int out_size) {
  const bf16* x   = (const bf16*)d_in[0];
  const bf16* Are = (const bf16*)d_in[1];
  const bf16* Aim = (const bf16*)d_in[2];
  const bf16* Bre = (const bf16*)d_in[3];
  const bf16* Bim = (const bf16*)d_in[4];
  const bf16* Cre = (const bf16*)d_in[5];
  const bf16* Cim = (const bf16*)d_in[6];
  const bf16* ldt = (const bf16*)d_in[7];
  const bf16* dsk = (const bf16*)d_in[8];
  const bf16* wg  = (const bf16*)d_in[10];
  const bf16* wu  = (const bf16*)d_in[11];
  const bf16* wd  = (const bf16*)d_in[12];

  static EncFn enc = nullptr;
  static void *p_hT = nullptr, *p_uT = nullptr, *p_xT = nullptr;
  if (!enc) {
    void* fn = nullptr; cudaDriverEntryPointQueryResult qr;
    cudaGetDriverEntryPoint("cuTensorMapEncodeTiled", &fn, cudaEnableDefault, &qr);
    enc = (EncFn)fn;
    cudaGetSymbolAddress(&p_hT, g_hT);
    cudaGetSymbolAddress(&p_uT, g_uT);
    cudaGetSymbolAddress(&p_xT, g_xT);
    cudaFuncSetAttribute(k_all, cudaFuncAttributeMaxDynamicSharedMemorySize, M_TOTAL);
  }
  CUtensorMap tmA, tmG, tmU, tmD, tmLu, tmLx;
  {
    uint64_t dims[2] = {DM * 16, SEQ / 16}, st[1] = {DM * 32};
    uint32_t box[2] = {32, 128};
    make_map(enc, &tmLu, p_uT, 2, dims, st, box, CU_TENSOR_MAP_SWIZZLE_NONE);
    make_map(enc, &tmLx, p_xT, 2, dims, st, box, CU_TENSOR_MAP_SWIZZLE_NONE);
  }
  {
    uint64_t dims[3] = {64, DM, SEQ / 64}, st[2] = {SEQ * 2, 128};
    uint32_t box[3] = {64, 64, 1};
    make_map(enc, &tmA, p_hT, 3, dims, st, box, CU_TENSOR_MAP_SWIZZLE_128B);
  }
  {
    uint64_t dims[2] = {FF, DM}, st[1] = {FF * 2};
    uint32_t box[2] = {64, 64};
    make_map(enc, &tmG, wg, 2, dims, st, box, CU_TENSOR_MAP_SWIZZLE_128B);
    make_map(enc, &tmU, wu, 2, dims, st, box, CU_TENSOR_MAP_SWIZZLE_128B);
  }
  {
    uint64_t dims[2] = {DM, FF}, st[1] = {DM * 2};
    uint32_t box[2] = {64, 32};
    make_map(enc, &tmD, wd, 2, dims, st, box, CU_TENSOR_MAP_SWIZZLE_128B);
  }
  static_assert(FR_BAR == M_BAR + 320 && FR_BAR + 16 <= M_TOTAL, "barrier placement");
  static_assert(FRONT_SMEM <= M_XB, "front phase must not touch the MLP barriers");
  launch_k(k_all, 132, 512, M_TOTAL, false, Are, Aim, Bre, Bim, Cre, Cim, ldt, dsk, x, wg, wu, wd, tmLu, tmLx, tmA, tmG, tmU, tmD, (bf16*)d_out);
}
```

```cpp
#include <cuda_runtime.h>
#include <cuda_bf16.h>
#include <cuda_fp16.h>
#include <cuda.h>
#include <stdint.h>

typedef __nv_bfloat16 bf16;

constexpr int SEQ = 2048;
constexpr int DM  = 448;
constexpr int NM  = 256;
constexpr int FF  = 1792;

__device__ __align__(1024) bf16  g_uT[DM * SEQ];
__device__ __align__(1024) bf16  g_xT[DM * SEQ];
__device__ __align__(1024) bf16  g_hT[DM * SEQ];
__device__ __align__(1024) bf16  g_P[SEQ * FF];
__device__ __align__(1024) bf16  g_dummy[16 * DM];
__device__ __align__(1024) float g_cs[2 * FF];

__device__ __forceinline__ uint32_t smem_u32(const void* p) { return (uint32_t)__cvta_generic_to_shared(p); }
__device__ __forceinline__ float bf16r(float v) { return __bfloat162float(__float2bfloat16_rn(v)); }
__device__ __forceinline__ float bflo(uint32_t w) { return __uint_as_float(w << 16); }
__device__ __forceinline__ float bfhi(uint32_t w) { return __uint_as_float(w & 0xffff0000u); }
__device__ __forceinline__ uint32_t pack_bf16(float lo, float hi) {
  uint32_t r; asm("cvt.rn.bf16x2.f32 %0, %1, %2;" : "=r"(r) : "f"(hi), "f"(lo)); return r;
}
__device__ __forceinline__ uint32_t pack_f16(float lo, float hi) {
  uint32_t r; asm("cvt.rn.f16x2.f32 %0, %1, %2;" : "=r"(r) : "f"(hi), "f"(lo)); return r;
}
__device__ __forceinline__ float ex2f(float x) { float r; asm("ex2.approx.ftz.f32 %0, %1;" : "=f"(r) : "f"(x)); return r; }
__device__ __forceinline__ float ln_rden(float var) {
  float sq, r;
  asm("sqrt.approx.ftz.f32 %0, %1;" : "=f"(sq) : "f"(bf16r(bf16r(var) + 1e-5f)));
  asm("rcp.approx.ftz.f32 %0, %1;" : "=f"(r) : "f"(bf16r(sq)));
  return r;
}
__device__ __forceinline__ uint32_t hadd2_bf16(uint32_t a, uint32_t b) {
  const __nv_bfloat162 r = __hadd2_rn(*reinterpret_cast<const __nv_bfloat162*>(&a), *reinterpret_cast<const __nv_bfloat162*>(&b));
  return *reinterpret_cast<const uint32_t*>(&r);
}
__device__ __forceinline__ void pdl_launch() { asm volatile("griddepcontrol.launch_dependents;"); }
__device__ __forceinline__ void pdl_wait() { asm volatile("griddepcontrol.wait;" ::: "memory"); }

__device__ __forceinline__ void mbar_init(uint32_t a, int c) { asm volatile("mbarrier.init.shared::cta.b64 [%0], %1;" ::"r"(a), "r"(c)); }
__device__ __forceinline__ void mbar_expect(uint32_t a, uint32_t bytes) {
  asm volatile("mbarrier.arrive.expect_tx.shared::cta.b64 _, [%0], %1;" ::"r"(a), "r"(bytes) : "memory");
}
__device__ __forceinline__ void mbar_arrive(uint32_t a) { asm volatile("mbarrier.arrive.shared::cta.b64 _, [%0];" ::"r"(a) : "memory"); }
__device__ __forceinline__ void mbar_arrive_cluster(uint32_t remote_a) {
  asm volatile("mbarrier.arrive.shared::cluster.b64 _, [%0];" ::"r"(remote_a) : "memory");
}
__device__ __forceinline__ void mbar_wait(uint32_t a, uint32_t ph) {
  uint32_t ok; int it = 0;
  do {
    asm volatile("{.reg .pred p; mbarrier.try_wait.parity.shared::cta.b64 p, [%1], %2; selp.u32 %0,1,0,p;}"
                 : "=r"(ok) : "r"(a), "r"(ph) : "memory");
  } while (!ok && ++it < (1 << 24));
}
__device__ __forceinline__ void flag_wait(const unsigned int* p, unsigned int target) {
  unsigned int v; int it = 0;
  asm volatile("ld.acquire.gpu.global.u32 %0, [%1];" : "=r"(v) : "l"(p) : "memory");
  if ((int)(v - target) >= 0) return;
  while (true) {
    __nanosleep(32);
    asm volatile("ld.relaxed.gpu.global.u32 %0, [%1];" : "=r"(v) : "l"(p) : "memory");
    if ((int)(v - target) >= 0 || ++it > (1 << 22)) break;
  }
  asm volatile("ld.acquire.gpu.global.u32 %0, [%1];" : "=r"(v) : "l"(p) : "memory");
}
__device__ __forceinline__ uint4 ld_relaxed_v4(const uint4* p) {
  uint4 v; asm volatile("ld.relaxed.gpu.global.v4.u32 {%0,%1,%2,%3}, [%4];" : "=r"(v.x), "=r"(v.y), "=r"(v.z), "=r"(v.w) : "l"(p) : "memory"); return v;
}
__device__ __forceinline__ void st_relaxed_v4(uint4* p, uint32_t a, uint32_t b, uint32_t c, uint32_t d) {
  asm volatile("st.relaxed.gpu.global.v4.u32 [%0], {%1,%2,%3,%4};" ::"l"(p), "r"(a), "r"(b), "r"(c), "r"(d) : "memory");
}
__device__ __forceinline__ uint32_t mapa(uint32_t a, uint32_t rank) {
  uint32_t r; asm volatile("mapa.shared::cluster.u32 %0, %1, %2;" : "=r"(r) : "r"(a), "r"(rank)); return r;
}
__device__ __forceinline__ void cluster_arrive() { asm volatile("barrier.cluster.arrive.relaxed.aligned;" ::: "memory"); }
__device__ __forceinline__ void cluster_wait() { asm volatile("barrier.cluster.wait.acquire.aligned;" ::: "memory"); }
__device__ __forceinline__ void fence_async() { asm volatile("fence.proxy.async.shared::cta;" ::: "memory"); }
__device__ __forceinline__ void named_bar(int id, int n) { asm volatile("bar.sync %0, %1;" ::"r"(id), "r"(n) : "memory"); }

__device__ __forceinline__ void tma2d(uint32_t dst, const CUtensorMap* tm, uint32_t bar, int c0, int c1) {
  asm volatile("cp.async.bulk.tensor.2d.shared::cluster.global.mbarrier::complete_tx::bytes [%0], [%1, {%3,%4}], [%2];"
               ::"r"(dst), "l"(tm), "r"(bar), "r"(c0), "r"(c1) : "memory");
}
__device__ __forceinline__ void tma3d(uint32_t dst, const CUtensorMap* tm, uint32_t bar, int c0, int c1, int c2) {
  asm volatile("cp.async.bulk.tensor.3d.shared::cluster.global.mbarrier::complete_tx::bytes [%0], [%1, {%3,%4,%5}], [%2];"
               ::"r"(dst), "l"(tm), "r"(bar), "r"(c0), "r"(c1), "r"(c2) : "memory");
}
__device__ __forceinline__ void tma3d_mc(uint32_t dst, const CUtensorMap* tm, uint32_t bar, int c0, int c1, int c2, uint16_t mask) {
  asm volatile("cp.async.bulk.tensor.3d.shared::cluster.global.mbarrier::complete_tx::bytes.multicast::cluster [%0], [%1, {%3,%4,%5}], [%2], %6;"
               ::"r"(dst), "l"(tm), "r"(bar), "r"(c0), "r"(c1), "r"(c2), "h"(mask) : "memory");
}
__device__ __forceinline__ void tma2d_store(const CUtensorMap* tm, uint32_t src, int c0, int c1) {
  asm volatile("cp.async.bulk.tensor.2d.global.shared::cta.bulk_group [%0, {%2,%3}], [%1];"
               ::"l"(tm), "r"(src), "r"(c0), "r"(c1) : "memory");
}
__device__ __forceinline__ void bulk_commit() { asm volatile("cp.async.bulk.commit_group;" ::: "memory"); }
template <int N> __device__ __forceinline__ void bulk_wait_read() { asm volatile("cp.async.bulk.wait_group.read %0;" ::"n"(N) : "memory"); }
template <int N> __device__ __forceinline__ void bulk_wait() { asm volatile("cp.async.bulk.wait_group %0;" ::"n"(N) : "memory"); }
__device__ __forceinline__ void prefetch_tm(const CUtensorMap* tm) { asm volatile("prefetch.tensormap [%0];" ::"l"(tm) : "memory"); }

__device__ __forceinline__ void wg_fence() { asm volatile("wgmma.fence.sync.aligned;" ::: "memory"); }
__device__ __forceinline__ void wg_commit() { asm volatile("wgmma.commit_group.sync.aligned;" ::: "memory"); }
template <int N> __device__ __forceinline__ void wg_wait() { asm volatile("wgmma.wait_group.sync.aligned %0;" ::"n"(N) : "memory"); }
__device__ __forceinline__ uint64_t mk_desc(uint32_t addr, uint32_t lbo, uint32_t sbo, uint32_t swz) {
  return (uint64_t)((addr & 0x3FFFF) >> 4) | ((uint64_t)(lbo >> 4) << 16) | ((uint64_t)(sbo >> 4) << 32) | ((uint64_t)swz << 62);
}
__device__ __forceinline__ void ldsm_x4(uint32_t a, uint32_t& r0, uint32_t& r1, uint32_t& r2, uint32_t& r3) {
  asm volatile("ldmatrix.sync.aligned.m8n8.x4.shared.b16 {%0,%1,%2,%3}, [%4];" : "=r"(r0), "=r"(r1), "=r"(r2), "=r"(r3) : "r"(a));
}
__device__ __forceinline__ void ldsm_x4_t(uint32_t a, uint32_t& r0, uint32_t& r1, uint32_t& r2, uint32_t& r3) {
  asm volatile("ldmatrix.sync.aligned.m8n8.x4.trans.shared.b16 {%0,%1,%2,%3}, [%4];" : "=r"(r0), "=r"(r1), "=r"(r2), "=r"(r3) : "r"(a));
}
__device__ __forceinline__ void ldsm_x2_t(uint32_t a, uint32_t& r0, uint32_t& r1) {
  asm volatile("ldmatrix.sync.aligned.m8n8.x2.trans.shared.b16 {%0,%1}, [%2];" : "=r"(r0), "=r"(r1) : "r"(a));
}
__device__ __forceinline__ void stsm_x4(uint32_t a, uint32_t r0, uint32_t r1, uint32_t r2, uint32_t r3) {
  asm volatile("stmatrix.sync.aligned.m8n8.x4.shared.b16 [%0], {%1,%2,%3,%4};" ::"r"(a), "r"(r0), "r"(r1), "r"(r2), "r"(r3) : "memory");
}
__device__ __forceinline__ void stsm_x2(uint32_t a, uint32_t r0, uint32_t r1) {
  asm volatile("stmatrix.sync.aligned.m8n8.x2.shared.b16 [%0], {%1,%2};" ::"r"(a), "r"(r0), "r"(r1) : "memory");
}
__device__ __forceinline__ uint32_t lds32(uint32_t a) { uint32_t r; asm volatile("ld.shared.u32 %0, [%1];" : "=r"(r) : "r"(a)); return r; }
__device__ __forceinline__ void mma_bf16(float (&c)[4], uint32_t a0, uint32_t a1, uint32_t a2, uint32_t a3, uint32_t b0, uint32_t b1) {
  asm volatile("mma.sync.aligned.m16n8k16.row.col.f32.bf16.bf16.f32 {%0,%1,%2,%3}, {%4,%5,%6,%7}, {%8,%9}, {%0,%1,%2,%3};"
               : "+f"(c[0]), "+f"(c[1]), "+f"(c[2]), "+f"(c[3]) : "r"(a0), "r"(a1), "r"(a2), "r"(a3), "r"(b0), "r"(b1));
}
__device__ __forceinline__ void mma_f16(float (&c)[4], uint32_t a0, uint32_t a1, uint32_t a2, uint32_t a3, uint32_t b0, uint32_t b1) {
  asm volatile("mma.sync.aligned.m16n8k16.row.col.f32.f16.f16.f32 {%0,%1,%2,%3}, {%4,%5,%6,%7}, {%8,%9}, {%0,%1,%2,%3};"
               : "+f"(c[0]), "+f"(c[1]), "+f"(c[2]), "+f"(c[3]) : "r"(a0), "r"(a1), "r"(a2), "r"(a3), "r"(b0), "r"(b1));
}
__device__ __forceinline__ void cp_async16(uint32_t dst, const void* src) {
  asm volatile("cp.async.cg.shared.global [%0], [%1], 16;" ::"r"(dst), "l"(src) : "memory");
}
__device__ __forceinline__ void cp_async_wait_all() { asm volatile("cp.async.wait_all;" ::: "memory"); }

__device__ unsigned int g_epoch;
__device__ unsigned int g_cnt[16];
__device__ unsigned int g_cnt2[256];
__device__ unsigned int g_done;

constexpr int LN_PITCH = 912;
constexpr int LN_STAT  = 16 * LN_PITCH;
constexpr int LN_SMEM  = LN_STAT + 7 * 128;
__device__ __forceinline__ void ln1_load(const bf16* __restrict__ x, int tile, unsigned char* sm) {
  const int r = (threadIdx.x >> 4) & 15, c = threadIdx.x & 15;
  const uint32_t dst = smem_u32(sm) + r * LN_PITCH + c * 16;
  const bf16* src = x + (size_t)(tile * 16 + r) * DM + c * 8;
#pragma unroll
  for (int k = 0; k < 4; k++)
    if (k < 3 || c < 8) cp_async16(dst + k * 256, src + k * 128);
}
__device__ __forceinline__ void ln1_tile(int tile, unsigned char* sm) {
  const uint32_t sb = smem_u32(sm);
  const int lane = threadIdx.x & 31, w = (threadIdx.x >> 5) - 8;
  const int g = lane >> 2, t = lane & 3;
  cp_async_wait_all();
  named_bar(14, 256);
  if (w < 7) {
    float s1[4] = {0.f, 0.f, 0.f, 0.f}, qa[4] = {0.f, 0.f, 0.f, 0.f}, qb[4] = {0.f, 0.f, 0.f, 0.f};
    const uint32_t ad = sb + ((lane & 7) + 8 * ((lane >> 3) & 1)) * LN_PITCH + (lane >> 4) * 16 + w * 128;
#pragma unroll
    for (int k = 0; k < 4; k++) {
      uint32_t a0, a1, a2, a3;
      ldsm_x4(ad + k * 32, a0, a1, a2, a3);
      mma_bf16(s1, a0, a1, a2, a3, 0x3f803f80u, 0x3f803f80u);
      mma_bf16(qa, a0, a1, a2, a3, a0, a2);
      mma_bf16(qb, a0, a1, a2, a3, a1, a3);
    }
    if (t == (g >> 1)) {
      float2* st = reinterpret_cast<float2*>(sm + LN_STAT) + w * 16;
      st[g]     = make_float2(s1[0], (g & 1) ? qa[1] : qa[0]);
      st[g + 8] = make_float2(s1[2], (g & 1) ? qb[3] : qb[2]);
    }
  }
  named_bar(14, 256);
  if (w < 7) {
    float mb[4], rd[4];
    {
      const float2* st = reinterpret_cast<const float2*>(sm + LN_STAT) + (lane & 15);
      float sx = 0.f, sy = 0.f;
#pragma unroll
      for (int i = 0; i < 7; i++) { const float2 p = st[16 * i]; sx += p.x; sy += p.y; }
      const float mean = sx * (1.0f / DM);
      const float var = fmaxf(sy * (1.0f / DM) - mean * mean, 0.f);
      const float m = bf16r(mean);
      const float r = ln_rden(var);
#pragma unroll
      for (int e = 0; e < 4; e++) {
        mb[e] = __shfl_sync(0xffffffffu, m, 4 * t + e);
        rd[e] = __shfl_sync(0xffffffffu, r, 4 * t + e);
      }
    }
    const int r8 = lane & 7;
    const int tok = 4 * (r8 >> 1) + (r8 & 1) + 2 * ((lane >> 3) & 1);
    const uint32_t ad = sb + tok * LN_PITCH + (w * 64 + (lane >> 4) * 8) * 2;
    const size_t go = (size_t)(tile * DM + w * 64 + g) * 16 + 4 * t;
#pragma unroll
    for (int k = 0; k < 4; k++) {
      uint32_t v[4];
      ldsm_x4_t(ad + k * 32, v[0], v[1], v[2], v[3]);
#pragma unroll
      for (int h = 0; h < 2; h++) {
        const uint32_t d0 = pack_bf16(bflo(v[2 * h]) - mb[0], bfhi(v[2 * h]) - mb[1]);
        const uint32_t d1 = pack_bf16(bflo(v[2 * h + 1]) - mb[2], bfhi(v[2 * h + 1]) - mb[3]);
        const size_t o = go + (size_t)(16 * k + 8 * h) * 16;
        *reinterpret_cast<uint2*>(g_uT + o) = make_uint2(pack_bf16(bflo(d0) * rd[0], bfhi(d0) * rd[1]), pack_bf16(bflo(d1) * rd[2], bfhi(d1) * rd[3]));
        *reinterpret_cast<uint2*>(g_xT + o) = make_uint2(v[2 * h], v[2 * h + 1]);
      }
    }
    asm volatile("bar.arrive 12, 256;" ::: "memory");
  } else {
    named_bar(12, 256);
    if (lane == 0) {
      asm volatile("fence.acq_rel.gpu;" ::: "memory");
      asm volatile("red.relaxed.gpu.global.add.u32 [%0], 1;" ::"l"(&g_cnt[7]) : "memory");
    }
    __syncwarp();
  }
}

constexpr int CS_SMEM = 448 * 64 + 16 * 128;
__device__ __forceinline__ void colsum_load(const bf16* __restrict__ wg, const bf16* __restrict__ wu, int b2, unsigned char* sm) {
  const bf16* W = (b2 >= 56 ? wu : wg) + (b2 % 56) * 32;
  const uint32_t sb = smem_u32(sm);
#pragma unroll
  for (int k = 0; k < 7; k++)
    cp_async16(sb + (threadIdx.x & 255) * 16 + k * 4096, W + (size_t)((threadIdx.x & 255) >> 2) * FF + (threadIdx.x & 3) * 8 + (size_t)k * 64 * FF);
}
__device__ __forceinline__ void colsum_reduce(unsigned char* sm) {
  const int lane = threadIdx.x & 31, w = (threadIdx.x >> 5) & 7;
  if (w >= 7) return;
  float acc[4][4];
#pragma unroll
  for (int i = 0; i < 4; i++) { acc[i][0] = acc[i][1] = acc[i][2] = acc[i][3] = 0.f; }
  const uint32_t ad = smem_u32(sm) + (w * 64 + (lane & 15)) * 64 + (lane >> 4) * 16;
#pragma unroll
  for (int k = 0; k < 4; k++) {
#pragma unroll
    for (int h = 0; h < 2; h++) {
      uint32_t b0, b1, b2, b3;
      ldsm_x4_t(ad + k * 1024 + h * 32, b0, b1, b2, b3);
      mma_bf16(acc[2 * h], 0x3f803f80u, 0x3f803f80u, 0x3f803f80u, 0x3f803f80u, b0, b1);
      mma_bf16(acc[2 * h + 1], 0x3f803f80u, 0x3f803f80u, 0x3f803f80u, 0x3f803f80u, b2, b3);
    }
  }
  if (lane < 4) {
    float* sf = reinterpret_cast<float*>(sm + 448 * 64) + w * 32 + 2 * lane;
#pragma unroll
    for (int i = 0; i < 4; i++) *reinterpret_cast<float2*>(sf + 8 * i) = make_float2(acc[i][0], acc[i][1]);
  }
}
__device__ __forceinline__ void colsum_store(int b2, unsigned char* sm) {
  const float* sf = reinterpret_cast<const float*>(sm + 448 * 64);
  const int lane = threadIdx.x & 31;
  float s = 0.f;
#pragma unroll
  for (int i = 0; i < 7; i++) s += sf[i * 32 + lane];
  g_cs[(b2 >= 56 ? FF : 0) + (b2 % 56) * 32 + lane] = s;
}
__device__ __forceinline__ void wgmma_rs_n96(float (&d)[48], uint32_t a0, uint32_t a1, uint32_t a2, uint32_t a3, uint64_t db, int sc) {
  asm volatile("{\n.reg .pred p;\nsetp.ne.b32 p, %53, 0;\n"
    "wgmma.mma_async.sync.aligned.m64n96k16.f32.bf16.bf16 {%0, %1, %2, %3, %4, %5, %6, %7, %8, %9, %10, %11, %12, %13, %14, %15, %16, %17, %18, %19, %20, %21, %22, %23, %24, %25, %26, %27, %28, %29, %30, %31, %32, %33, %34, %35, %36, %37, %38, %39, %40, %41, %42, %43, %44, %45, %46, %47}, {%48, %49, %50, %51}, %52, p, 1, 1, 1;\n}\n"
    : "+f"(d[0]), "+f"(d[1]), "+f"(d[2]), "+f"(d[3]), "+f"(d[4]), "+f"(d[5]), "+f"(d[6]), "+f"(d[7]), "+f"(d[8]), "+f"(d[9]), "+f"(d[10]), "+f"(d[11]), "+f"(d[12]), "+f"(d[13]), "+f"(d[14]), "+f"(d[15]), "+f"(d[16]), "+f"(d[17]), "+f"(d[18]), "+f"(d[19]), "+f"(d[20]), "+f"(d[21]), "+f"(d[22]), "+f"(d[23]), "+f"(d[24]), "+f"(d[25]), "+f"(d[26]), "+f"(d[27]), "+f"(d[28]), "+f"(d[29]), "+f"(d[30]), "+f"(d[31]), "+f"(d[32]), "+f"(d[33]), "+f"(d[34]), "+f"(d[35]), "+f"(d[36]), "+f"(d[37]), "+f"(d[38]), "+f"(d[39]), "+f"(d[40]), "+f"(d[41]), "+f"(d[42]), "+f"(d[43]), "+f"(d[44]), "+f"(d[45]), "+f"(d[46]), "+f"(d[47])
    : "r"(a0), "r"(a1), "r"(a2), "r"(a3), "l"(db), "r"(sc));
}
__device__ __forceinline__ void wgmma_rs_n128(float (&d)[64], uint32_t a0, uint32_t a1, uint32_t a2, uint32_t a3, uint64_t db, int sc) {
  asm volatile("{\n.reg .pred p;\nsetp.ne.b32 p, %69, 0;\n"
    "wgmma.mma_async.sync.aligned.m64n128k16.f32.bf16.bf16 {%0, %1, %2, %3, %4, %5, %6, %7, %8, %9, %10, %11, %12, %13, %14, %15, %16, %17, %18, %19, %20, %21, %22, %23, %24, %25, %26, %27, %28, %29, %30, %31, %32, %33, %34, %35, %36, %37, %38, %39, %40, %41, %42, %43, %44, %45, %46, %47, %48, %49, %50, %51, %52, %53, %54, %55, %56, %57, %58, %59, %60, %61, %62, %63}, {%64, %65, %66, %67}, %68, p, 1, 1, 1;\n}\n"
    : "+f"(d[0]), "+f"(d[1]), "+f"(d[2]), "+f"(d[3]), "+f"(d[4]), "+f"(d[5]), "+f"(d[6]), "+f"(d[7]), "+f"(d[8]), "+f"(d[9]), "+f"(d[10]), "+f"(d[11]), "+f"(d[12]), "+f"(d[13]), "+f"(d[14]), "+f"(d[15]), "+f"(d[16]), "+f"(d[17]), "+f"(d[18]), "+f"(d[19]), "+f"(d[20]), "+f"(d[21]), "+f"(d[22]), "+f"(d[23]), "+f"(d[24]), "+f"(d[25]), "+f"(d[26]), "+f"(d[27]), "+f"(d[28]), "+f"(d[29]), "+f"(d[30]), "+f"(d[31]), "+f"(d[32]), "+f"(d[33]), "+f"(d[34]), "+f"(d[35]), "+f"(d[36]), "+f"(d[37]), "+f"(d[38]), "+f"(d[39]), "+f"(d[40]), "+f"(d[41]), "+f"(d[42]), "+f"(d[43]), "+f"(d[44]), "+f"(d[45]), "+f"(d[46]), "+f"(d[47]), "+f"(d[48]), "+f"(d[49]), "+f"(d[50]), "+f"(d[51]), "+f"(d[52]), "+f"(d[53]), "+f"(d[54]), "+f"(d[55]), "+f"(d[56]), "+f"(d[57]), "+f"(d[58]), "+f"(d[59]), "+f"(d[60]), "+f"(d[61]), "+f"(d[62]), "+f"(d[63])
    : "r"(a0), "r"(a1), "r"(a2), "r"(a3), "l"(db), "r"(sc));
}
__device__ __forceinline__ void wgmma_rs_n112(float (&d)[56], uint32_t a0, uint32_t a1, uint32_t a2, uint32_t a3, uint64_t db, int sc) {
  asm volatile("{\n.reg .pred p;\nsetp.ne.b32 p, %61, 0;\n"
    "wgmma.mma_async.sync.aligned.m64n112k16.f32.bf16.bf16 {%0, %1, %2, %3, %4, %5, %6, %7, %8, %9, %10, %11, %12, %13, %14, %15, %16, %17, %18, %19, %20, %21, %22, %23, %24, %25, %26, %27, %28, %29, %30, %31, %32, %33, %34, %35, %36, %37, %38, %39, %40, %41, %42, %43, %44, %45, %46, %47, %48, %49, %50, %51, %52, %53, %54, %55}, {%56, %57, %58, %59}, %60, p, 1, 1, 1;\n}\n"
    : "+f"(d[0]), "+f"(d[1]), "+f"(d[2]), "+f"(d[3]), "+f"(d[4]), "+f"(d[5]), "+f"(d[6]), "+f"(d[7]), "+f"(d[8]), "+f"(d[9]), "+f"(d[10]), "+f"(d[11]), "+f"(d[12]), "+f"(d[13]), "+f"(d[14]), "+f"(d[15]), "+f"(d[16]), "+f"(d[17]), "+f"(d[18]), "+f"(d[19]), "+f"(d[20]), "+f"(d[21]), "+f"(d[22]), "+f"(d[23]), "+f"(d[24]), "+f"(d[25]), "+f"(d[26]), "+f"(d[27]), "+f"(d[28]), "+f"(d[29]), "+f"(d[30]), "+f"(d[31]), "+f"(d[32]), "+f"(d[33]), "+f"(d[34]), "+f"(d[35]), "+f"(d[36]), "+f"(d[37]), "+f"(d[38]), "+f"(d[39]), "+f"(d[40]), "+f"(d[41]), "+f"(d[42]), "+f"(d[43]), "+f"(d[44]), "+f"(d[45]), "+f"(d[46]), "+f"(d[47]), "+f"(d[48]), "+f"(d[49]), "+f"(d[50]), "+f"(d[51]), "+f"(d[52]), "+f"(d[53]), "+f"(d[54]), "+f"(d[55])
    : "r"(a0), "r"(a1), "r"(a2), "r"(a3), "l"(db), "r"(sc));
}

struct cplx { float re, im; };
__device__ __forceinline__ cplx cmul(cplx a, cplx b) {
  cplx r; r.re = a.re * b.re - a.im * b.im; r.im = a.re * b.im + a.im * b.re; return r;
}
__device__ __forceinline__ cplx zpow_acc(float a2, float bt, float c) {
  float mag = ex2f(a2 * c);
  float tr = bt * c;
  tr -= rintf(tr);
  float ang = tr * 6.283185307179586f;
  cplx r; r.re = mag * __cosf(ang); r.im = mag * __sinf(ang); return r;
}

constexpr int SB_TAB  = 0;
constexpr int SB_WREG = 7168;
constexpr int UZ = 40;
constexpr int SB_U    = 4 * SB_WREG;
constexpr int SB_KV   = SB_U + 172 * 36;
constexpr int SB_TOTAL = (SB_KV + 644 * 4 + 127) / 128 * 128;
constexpr int SB_F3   = 0;
constexpr int SB_F2   = 1792;
constexpr int SB_Y    = 4096;
constexpr int SB_KD   = SB_Y;
constexpr int SB_KDO  = SB_KD + 2240;
constexpr int FR_LN = 4 * SB_TOTAL;
constexpr int FR_CS = (FR_LN + LN_SMEM + 127) / 128 * 128;
constexpr int FR_X = FR_CS + CS_SMEM;
constexpr int FRONT_SMEM = FR_X + 16384;
constexpr int FR_BAR = 229120 + 320;

__device__ __forceinline__ int rowaddr(int r) { return 32 * r + 16 * (r >> 2); }
struct hc { __half2 re, im; };
__device__ __forceinline__ hc bcast(cplx a) { hc r; r.re = __float2half2_rn(a.re); r.im = __float2half2_rn(a.im); return r; }
__device__ __forceinline__ hc hmul(hc v, hc s) {
  hc r;
  r.re = __hfma2(v.re, s.re, __hneg2(__hmul2(v.im, s.im)));
  r.im = __hfma2(v.re, s.im, __hmul2(v.im, s.re));
  return r;
}
__device__ __forceinline__ uint32_t h2u(__half2 h) { return *reinterpret_cast<uint32_t*>(&h); }
__device__ __forceinline__ void gen8(unsigned char* p, cplx s, cplx r1, hc r1sq, hc r2) {
  const cplx v1 = cmul(s, r1);
  hc p0; p0.re = __floats2half2_rn(s.re, v1.re); p0.im = __floats2half2_rn(s.im, v1.im);
  const hc p1 = hmul(p0, r1sq), p2 = hmul(p0, r2), p3 = hmul(p1, r2);
  *reinterpret_cast<uint4*>(p) = make_uint4(h2u(p0.re), h2u(p1.re), h2u(p2.re), h2u(p3.re));
  *reinterpret_cast<uint4*>(p + 8 * 112) = make_uint4(h2u(p0.im), h2u(p1.im), h2u(p2.im), h2u(p3.im));
}
__device__ __forceinline__ cplx csq(cplx a) { cplx r; r.re = a.re * a.re - a.im * a.im; r.im = 2.f * a.re * a.im; return r; }
__device__ __forceinline__ cplx cconj(cplx a) { a.im = -a.im; return a; }
__device__ __forceinline__ uint2 lds64(uint32_t a) { uint2 r; asm volatile("ld.shared.v2.u32 {%0,%1}, [%2];" : "=r"(r.x), "=r"(r.y) : "r"(a)); return r; }

__device__ __forceinline__ void mlp_bar_init(uint32_t base) {
  if ((threadIdx.x & 31) == 0 && (threadIdx.x >> 7) == 1) {
#pragma unroll 1
    for (int b = (threadIdx.x >> 5) - 4; b < 36; b += 4) mbar_init(base + 8 * b, ((b >= 10 && b < 13) || b == 28 || b >= 32) ? 2 : 1);
    asm volatile("fence.mbarrier_init.release.cluster;" ::: "memory");
  }
  __syncwarp();
}

__device__ __forceinline__ void front_phase(const bf16* __restrict__ Are, const bf16* __restrict__ Aim,
                                             const bf16* __restrict__ Bre, const bf16* __restrict__ Bim,
                                             const bf16* __restrict__ Cre, const bf16* __restrict__ Cim,
                                             const bf16* __restrict__ log_dt, const bf16* __restrict__ Dskip,
                                             const bf16* __restrict__ x, const bf16* __restrict__ wg,
                                             const bf16* __restrict__ wu, const bf16* __restrict__ wd,
                                             const CUtensorMap& tmU, const CUtensorMap& tmX) {
  extern __shared__ __align__(1024) unsigned char smem_all[];
  const int sub = threadIdx.x >> 7;
  const int tid = threadIdx.x & 127, lane = tid & 31;
  const int bar = 1 + sub;
  unsigned char* sm = smem_all + sub * SB_TOTAL;
  const uint32_t sbase = smem_u32(sm);
  const int w = ((tid >> 5) + sub) & 3;
  const int g = lane >> 2, t = lane & 3;
  const bool upper = threadIdx.x >= 256;
  const int hbar = upper ? 14 : 13;
  const bool do_ln = upper && blockIdx.x < 128;
  if (do_ln) ln1_load(x, blockIdx.x, smem_all + FR_LN);
  if (blockIdx.x >= 112) {
    mlp_bar_init(smem_u32(smem_all) + FR_BAR - 320);
    if (do_ln) ln1_tile(blockIdx.x, smem_all + FR_LN);
    if (upper) named_bar(hbar, 256);
    const int t0 = (blockIdx.x - 112) + (upper ? 20 : 0);
    unsigned char* cs = smem_all + (upper ? 3 * CS_SMEM : 0);
#pragma unroll
    for (int i = 0; i < 3; i++)
      if (t0 + 40 * i < 112) colsum_load(wg, wu, t0 + 40 * i, cs + i * CS_SMEM);
    for (int i = (blockIdx.x - 112) * 512 + threadIdx.x; i < FF * DM * 2 / 128; i += 20 * 512)
      asm volatile("prefetch.global.L2 [%0];" ::"l"(reinterpret_cast<const char*>(wd) + (size_t)i * 128));
    cp_async_wait_all();
    named_bar(hbar, 256);
#pragma unroll
    for (int i = 0; i < 3; i++)
      if (t0 + 40 * i < 112) colsum_reduce(cs + i * CS_SMEM);
    named_bar(hbar, 256);
    const int wi = (threadIdx.x >> 5) & 7;
    if (wi < 3 && t0 + 40 * wi < 112) colsum_store(t0 + 40 * wi, cs + wi * CS_SMEM);
    named_bar(hbar, 256);
    if ((threadIdx.x & 255) == 0) {
      asm volatile("fence.acq_rel.gpu;" ::: "memory");
      asm volatile("red.relaxed.gpu.global.add.u32 [%0], 1;" ::"l"(&g_cnt[8]) : "memory");
    }
    return;
  }
  const int d = blockIdx.x * 4 + sub;
  if ((threadIdx.x & 255) == 0) mbar_init(smem_u32(smem_all) + FR_BAR + (upper ? 8 : 0), 1);
  const int pidx = (d * NM + 64 * w) / 2 + lane;
  const uint32_t pAre = __ldg(reinterpret_cast<const uint32_t*>(Are) + pidx), pAim = __ldg(reinterpret_cast<const uint32_t*>(Aim) + pidx);
  const uint32_t pBre = __ldg(reinterpret_cast<const uint32_t*>(Bre) + pidx), pBim = __ldg(reinterpret_cast<const uint32_t*>(Bim) + pidx);
  const uint32_t pCre = __ldg(reinterpret_cast<const uint32_t*>(Cre) + pidx), pCim = __ldg(reinterpret_cast<const uint32_t*>(Cim) + pidx);
  const bf16 ldt_raw = log_dt[d];
  mlp_bar_init(smem_u32(smem_all) + FR_BAR - 320);
  const float dt = bf16r(expf(__bfloat162float(ldt_raw)));
  const uint32_t dsk2 = (uint32_t)__bfloat16_as_ushort(Dskip[d]) * 0x10001u;
  if (upper) ln1_tile(blockIdx.x, smem_all + FR_LN);
  if (tid < 90) *reinterpret_cast<uint4*>(sm + SB_U + tid * 16) = make_uint4(0, 0, 0, 0);
  if (tid >= 96 && tid < 105) *reinterpret_cast<uint4*>(sm + SB_U + 168 * 36 + (tid - 96) * 16) = make_uint4(0, 0, 0, 0);
  float w0re, w0im, w1re, w1im;
  {
    const float br0 = dt * bflo(pBre), bi0 = dt * bflo(pBim), br1 = dt * bfhi(pBre), bi1 = dt * bfhi(pBim);
    w0re = bflo(pCre) * br0 - bflo(pCim) * bi0; w0im = bflo(pCre) * bi0 + bflo(pCim) * br0;
    w1re = bfhi(pCre) * br1 - bfhi(pCim) * bi1; w1im = bfhi(pCre) * bi1 + bfhi(pCim) * br1;
  }
  float mx = fmaxf(fmaxf(fabsf(w0re), fabsf(w0im)), fmaxf(fabsf(w1re), fabsf(w1im)));
#pragma unroll
  for (int o = 16; o > 0; o >>= 1) mx = fmaxf(mx, __shfl_xor_sync(0xffffffffu, mx, o));
  int ex = (__float_as_uint(mx) >> 23) & 0xff;
  ex = min(max(ex, 1), 252);
  const float scale = __uint_as_float((uint32_t)(253 - ex) << 23);
  const float inv_scale = __uint_as_float((uint32_t)(ex + 1) << 23);

  float acc[5][4];
#pragma unroll
  for (int i = 0; i < 5; i++) { acc[i][0] = acc[i][1] = acc[i][2] = acc[i][3] = 0.f; }
  float k2048 = 0.f;
  unsigned char* tabw = sm + SB_TAB + w * SB_WREG;
  const uint32_t ldA = sbase + SB_TAB + w * SB_WREG + ((lane & 7) + 8 * ((lane >> 4) & 1)) * 112 + ((lane >> 3) & 1) * 16;
  const uint32_t ldB = sbase + SB_TAB + w * SB_WREG + ((lane & 7) + 8 * ((lane >> 3) & 1)) * 112 + 32 + (lane >> 4) * 16;
#pragma unroll 1
  for (int r = 0; r < 2; r++) {
    {
      const float a2 = dt * (r ? bfhi(pAre) : bflo(pAre)) * 1.4426950408889634f;
      const float bt = dt * (r ? bfhi(pAim) : bflo(pAim)) * 0.15915494309189535f;
      cplx W; W.re = (r ? w1re : w0re) * scale; W.im = -(r ? w1im : w0im) * scale;
      unsigned char* rec = tabw + ((lane >> 3) * 16 + (lane & 7)) * 112;
      const cplx y1 = zpow_acc(a2, -bt, 1.f), z8 = zpow_acc(a2, bt, 8.f), y128 = zpow_acc(a2, -bt, 128.f);
      const cplx y512 = zpow_acc(a2, -bt, 512.f), y1024 = zpow_acc(a2, -bt, 1024.f);
      const cplx z16 = csq(z8), z32 = csq(z16), z64 = csq(z32);
      const cplx y2 = csq(y1), y4 = csq(y2), y256 = csq(y128);
      cplx one; one.re = 1.f; one.im = 0.f;
      const hc h16 = bcast(z16), h32 = bcast(z32), h2 = bcast(y2), h4 = bcast(y4);
      const hc h128 = bcast(y128), h256 = bcast(y256), h512 = bcast(y512);
      gen8(rec, one, z8, h16, h32);
      gen8(rec + 16, z64, z8, h16, h32);
      gen8(rec + 32, W, y1, h2, h4);
      gen8(rec + 48, cmul(W, y128), y1, h2, h4);
      gen8(rec + 64, cmul(W, y256), y2, h4, h128);
      gen8(rec + 80, cmul(W, y512), y128, h256, h4);
      const cplx w1024 = cmul(W, y1024);
      gen8(rec + 96, w1024, y128, h256, h512);
      k2048 += w1024.re * y1024.re - w1024.im * y1024.im;
    }
    __syncwarp();
#pragma unroll
    for (int ks = 0; ks < 4; ks++) {
      uint32_t a0, a1, a2, a3, b0, b1, b2, b3;
      ldsm_x4_t(ldA + ks * 1792, a0, a1, a2, a3);
      ldsm_x4_t(ldB + ks * 1792, b0, b1, b2, b3);
      mma_f16(acc[0], a0, a1, a2, a3, b0, b1);
      mma_f16(acc[1], a0, a1, a2, a3, b2, b3);
      ldsm_x4_t(ldB + ks * 1792 + 32, b0, b1, b2, b3);
      mma_f16(acc[2], a0, a1, a2, a3, b0, b1);
      mma_f16(acc[3], a0, a1, a2, a3, b2, b3);
      ldsm_x2_t(ldB + ks * 1792 + 64, b0, b1);
      mma_f16(acc[4], a0, a1, a2, a3, b0, b1);
    }
    __syncwarp();
  }
  {
    float* red = reinterpret_cast<float*>(tabw);
#pragma unroll
    for (int hr = 0; hr < 2; hr++) {
      const int row = g + 8 * hr;
      *reinterpret_cast<float2*>(red + 8 * row + 2 * t) = make_float2(acc[0][2 * hr] * inv_scale, acc[0][2 * hr + 1] * inv_scale);
      *reinterpret_cast<float2*>(red + 128 + 8 * row + 2 * t) = make_float2(acc[1][2 * hr] * inv_scale, acc[1][2 * hr + 1] * inv_scale);
      *reinterpret_cast<float2*>(red + 256 + 64 * (t >> 1) + 2 * (t & 1) + 4 * row) = make_float2(acc[2][2 * hr] * inv_scale, acc[2][2 * hr + 1] * inv_scale);
      red[384 + 64 * (t & 1) + (t >> 1) + 2 * row] = acc[3][2 * hr] * inv_scale;
      red[384 + 64 * (t & 1) + 32 + (t >> 1) + 2 * row] = acc[3][2 * hr + 1] * inv_scale;
      red[512 + 32 * t + row] = acc[4][2 * hr] * inv_scale;
      red[512 + 32 * t + 16 + row] = acc[4][2 * hr + 1] * inv_scale;
    }
#pragma unroll
    for (int o = 16; o > 0; o >>= 1) k2048 += __shfl_xor_sync(0xffffffffu, k2048, o);
    if (lane == 0) red[640] = k2048 * inv_scale;
  }
  const uint32_t ubar = smem_u32(smem_all) + FR_BAR + (upper ? 8 : 0);
  const int ustg = upper ? FR_LN : FR_CS;
  if ((threadIdx.x & 255) == 0) {
    flag_wait(&g_cnt[7], (__ldcg(&g_epoch) + 1u) * 128u);
    asm volatile("fence.proxy.async.global;" ::: "memory");
    mbar_expect(ubar, 16384);
    tma2d(smem_u32(smem_all) + ustg, &tmU, ubar, (blockIdx.x * 4 + (sub & 2)) * 16, 0);
    tma2d(smem_u32(smem_all) + FR_X + (upper ? 8192 : 0), &tmX, ubar, (blockIdx.x * 4 + (sub & 2)) * 16, 0);
  }
  __syncwarp();
  named_bar(bar, 128);
  float* Kv = reinterpret_cast<float*>(sm + SB_KV);
  {
    const float* r0 = reinterpret_cast<const float*>(sm + SB_TAB);
    constexpr int WS = SB_WREG / 4;
    const float4 a = *reinterpret_cast<const float4*>(r0 + 4 * tid), b = *reinterpret_cast<const float4*>(r0 + WS + 4 * tid);
    const float4 c = *reinterpret_cast<const float4*>(r0 + 2 * WS + 4 * tid), e = *reinterpret_cast<const float4*>(r0 + 3 * WS + 4 * tid);
    *reinterpret_cast<float4*>(Kv + 4 * tid) =
        make_float4((a.x + b.x) + (c.x + e.x), (a.y + b.y) + (c.y + e.y), (a.z + b.z) + (c.z + e.z), (a.w + b.w) + (c.w + e.w));
    const int i = 512 + tid;
    Kv[i] = (r0[i] + r0[WS + i]) + (r0[2 * WS + i] + r0[3 * WS + i]);
    if (tid == 0) Kv[640] = (r0[640] + r0[WS + 640]) + (r0[2 * WS + 640] + r0[3 * WS + 640]);
  }
  named_bar(bar, 128);
  {
    auto tap_idx = [](int j) { const int m = j >> 1; const int r = (j & 1) ? m + (m & 1) : m; return min(max(j < 256 ? j : 128 + r, 0), 640); };
    float kd[3][3], f3[3], f2[3];
#pragma unroll
    for (int it = 0; it < 3; it++) {
      const int j = 528 - 2 * (tid + 128 * it);
#pragma unroll
      for (int e = 0; e < 3; e++) kd[it][e] = Kv[tap_idx(j + 1 - e)];
    }
    const int fa = tid >= 48, xa = tid - 48 * fa, ja = 144 - 2 * xa;
    const int fb = tid >> 6, xb = tid & 63, jb = 160 - 2 * xb;
#pragma unroll
    for (int e = 0; e < 3; e++) {
      f3[e] = Kv[min(max(384 + fa + 2 * (ja + 1 - e), 0), 640)];
      f2[e] = Kv[min(256 + fb + 2 * (jb + 1 - e), 640)];
    }
    const float k512 = Kv[384];
    uint32_t* ee = reinterpret_cast<uint32_t*>(sm + SB_KD);
#pragma unroll
    for (int it = 0; it < 3; it++) {
      const int x = tid + 128 * it, j = 528 - 2 * x;
      const float k0 = (j >= -1 && j <= 508) ? kd[it][0] : 0.f;
      float k1 = (j >= 0 && j <= 510) ? kd[it][1] : 0.f;
      const float k2 = (j >= 1 && j <= 510) ? kd[it][2] : 0.f;
      if (j == 510) k1 -= k512;
      const uint32_t we = pack_bf16(k1, k2), wo = pack_bf16(k0, k1);
      if (x < 272) { ee[2 * x] = we; ee[560 + 2 * x] = wo; }
      if (x < 272 && x >= 4) { ee[2 * x - 7] = we; ee[560 + 2 * x - 7] = wo; }
    }
    {
      const int hi = 128 - fa;
      const float k0 = (ja + 1 >= 64 && ja + 1 <= hi) ? f3[0] : 0.f, k1 = (ja >= 64 && ja <= hi) ? f3[1] : 0.f;
      const float k2 = (ja - 1 >= 64 && ja - 1 <= hi) ? f3[2] : 0.f;
      const uint32_t we = pack_bf16(k1, k2), wo = pack_bf16(k0, k1);
      uint32_t* p = reinterpret_cast<uint32_t*>(sm + SB_F3) + fa * 224;
      if (tid < 96) { p[2 * xa] = we; p[112 + 2 * xa] = wo; }
      if (tid < 96 && xa < 44) { p[2 * xa + 9] = we; p[112 + 2 * xa + 9] = wo; }
    }
    {
      const float k0 = (jb + 1 >= 64 && jb + 1 <= 127) ? f2[0] : 0.f, k1 = (jb >= 64 && jb <= 127) ? f2[1] : 0.f;
      const float k2 = (jb - 1 >= 64 && jb - 1 <= 127) ? f2[2] : 0.f;
      const uint32_t we = pack_bf16(k1, k2), wo = pack_bf16(k0, k1);
      uint32_t* p = reinterpret_cast<uint32_t*>(sm + SB_F2) + fb * 288;
      p[2 * xb] = we; p[144 + 2 * xb] = wo;
      p[2 * xb + 17] = we; p[144 + 2 * xb + 17] = wo;
    }
  }
  const float k1024 = Kv[512];
  named_bar(hbar, 256);
  mbar_wait(ubar, 0);
#pragma unroll
  for (int k = 0; k < 2; k++) {
    const int c = tid + 128 * k;
    *reinterpret_cast<uint4*>(sm + SB_U + rowaddr((c >> 1) + UZ) + (c & 1) * 16) =
        *reinterpret_cast<const uint4*>(smem_all + ustg + (c >> 1) * 64 + (sub & 1) * 32 + (c & 1) * 16);
  }
  named_bar(hbar, 256);
  const int krow = (lane & 7) + 8 * ((lane >> 3) & 1);
  if (w < 2) {
    float acd[4][2][4];
#pragma unroll
    for (int c = 0; c < 4; c++)
#pragma unroll
      for (int i = 0; i < 2; i++)
#pragma unroll
        for (int e = 0; e < 4; e++) acd[c][i][e] = 0.f;
    const uint32_t aQ = sbase + SB_U + rowaddr(UZ + 64 * w + 4 * krow) + (lane >> 4) * 16;
    const uint32_t pb = sbase + ((g & 1) ? SB_KDO + ((529 - g) / 2 + t) * 8 : SB_KD + ((528 - g) / 2 + t) * 8);
    uint32_t Q[36][4];
#define QOFF(j) (32 * (j) + 16 * (((j) + 64) / 4 - 16))
#pragma unroll
    for (int n = 0; n < 5; n++) ldsm_x4(aQ + QOFF(3 - n), Q[n][0], Q[n][1], Q[n][2], Q[n][3]);
#pragma unroll
    for (int q = 0; q < 33; q++) {
      if (q + 5 < 36) ldsm_x4(aQ + QOFF(3 - (q + 5)), Q[q + 5][0], Q[q + 5][1], Q[q + 5][2], Q[q + 5][3]);
      const uint2 e0 = lds64(pb - 32 * (2 * q));
      const uint2 e1 = lds64(pb - 32 * (2 * q + 1));
#pragma unroll
      for (int c = 0; c < 4; c++) {
        mma_bf16(acd[c][0], Q[3 - c + q][0], Q[3 - c + q][1], Q[3 - c + q][2], Q[3 - c + q][3], e0.x, e0.y);
        mma_bf16(acd[c][1], Q[3 - c + q][0], Q[3 - c + q][1], Q[3 - c + q][2], Q[3 - c + q][3], e1.x, e1.y);
      }
    }
#undef QOFF
    const int yl = (64 * (16 * w + g) + 2 * t + 16 * (g & 1) + 8 * ((g >> 1) & 1)) * 4;
    unsigned char* yb = sm + SB_Y + 8192;
#pragma unroll
    for (int c = 0; c < 4; c++)
#pragma unroll
      for (int nu = 0; nu < 2; nu++)
#pragma unroll
        for (int hr = 0; hr < 2; hr++)
          *reinterpret_cast<float2*>(yb + ((yl ^ ((16 * c + 8 * (nu ^ (c >> 1))) * 4)) + hr * 2048)) = make_float2(acd[c][nu][2 * hr], acd[c][nu][2 * hr + 1]);
  } else {
    const int yl = (16 * (g ^ ((g >> 2) & 1)) + 2 * t + 8 * ((g >> 1) & 1)) * 4;
    if (w == 2) {
      float ac[7][2][4];
#pragma unroll
      for (int T = 0; T < 7; T++)
#pragma unroll
        for (int i = 0; i < 2; i++)
#pragma unroll
          for (int e = 0; e < 4; e++) ac[T][i][e] = 0.f;
      uint32_t BA[2][4];
#pragma unroll
      for (int ks = 0; ks < 2; ks++)
#pragma unroll
        for (int r = 0; r < 4; r++) {
          uint32_t v = 0;
#pragma unroll
          for (int e = 0; e < 2; e++) {
            const int dlt = (2 * t + e + 8 * (r >> 1) + 16 * ks - 8) - g;
            const bool on = (r & 1) ? (dlt >= -5 && dlt <= -3) : (dlt >= -2 && dlt <= 2);
            v |= on ? (0x3f80u << (16 * e)) : 0u;
          }
          BA[ks][r] = v;
        }
      const int chl = 2 * UZ + (lane & 7) + (lane >> 3) - 1;
      const uint32_t ub = sbase + SB_U + rowaddr(chl >> 1) + (chl & 1) * 16;
      const uint32_t fb = sbase + SB_F2 + (80 - (g - t)) * 8;
#pragma unroll
      for (int sp = 0; sp < 2; sp++) {
        uint32_t bb[2][7][2];
#pragma unroll
        for (int i = 0; i < 7 - sp; i++) {
          const int beta = 11 - sp - 2 * i;
#pragma unroll
          for (int o = 0; o < 2; o++) {
            uint32_t u0, u1, u2, u3;
            ldsm_x4(ub + (2 * beta + o) * 144, u0, u1, u2, u3);
            float z[4] = {0.f, 0.f, 0.f, 0.f};
            mma_bf16(z, BA[0][0], BA[0][1], BA[0][2], BA[0][3], u0, u1);
            mma_bf16(z, BA[1][0], BA[1][1], BA[1][2], BA[1][3], u2, u3);
            bb[0][i][o] = pack_bf16(z[0], z[1]);
            bb[1][i][o] = pack_bf16(z[2], z[3]);
          }
        }
#pragma unroll
        for (int f = 0; f < 2; f++) {
#pragma unroll
          for (int k = 0; k < 3; k++) {
#pragma unroll
            for (int nu = 0; nu < 2; nu++) {
              const uint2 A01 = lds64(fb + f * 1152 + nu * 576 - 32 * (6 + 2 * (2 * k + sp)));
              const uint2 A23 = lds64(fb + f * 1152 + nu * 576 - 32 * (5 + 2 * (2 * k + sp)));
#pragma unroll
              for (int i = 0; i < 7 - sp; i++) {
                const int T = 7 - i + k;
                if (T <= 7) mma_bf16(ac[T - 1][nu], A01.x, A01.y, A23.x, A23.y, bb[f][i][0], bb[f][i][1]);
              }
            }
          }
        }
      }
      named_bar(5 + bar, 96);
      unsigned char* yb = sm + SB_Y;
#pragma unroll
      for (int T = 0; T <= 7; T++)
#pragma unroll
        for (int nu = 0; nu < 2; nu++)
#pragma unroll
          for (int hr = 0; hr < 2; hr++)
            *reinterpret_cast<float2*>(yb + ((yl ^ ((8 * (nu ^ hr)) * 4)) + (16 * T + 8 * hr) * 64)) =
                T ? make_float2(ac[T ? T - 1 : 0][nu][2 * hr], ac[T ? T - 1 : 0][nu][2 * hr + 1]) : make_float2(0.f, 0.f);
    } else {
      float ac[5][2][4];
#pragma unroll
      for (int T = 0; T < 5; T++)
#pragma unroll
        for (int i = 0; i < 2; i++)
#pragma unroll
          for (int e = 0; e < 4; e++) ac[T][i][e] = 0.f;
      const uint32_t fb = sbase + SB_F3 + ((g & 1) ? 448 + ((145 - g) / 2 + t) * 8 : ((144 - g) / 2 + t) * 8);
      uint32_t ur[3];
#pragma unroll
      for (int sg = 0; sg < 3; sg++) ur[sg] = sbase + SB_U + rowaddr(UZ + (lane & 7) + 8 * (lane >> 4) + sg - 1) + ((lane >> 3) & 1) * 16;
#pragma unroll 1
      for (int f = 0; f < 2; f++) {
        uint32_t BA[3][4];
        const int lo = f ? -11 : -4, hi = f ? -5 : 4;
#pragma unroll
        for (int sg = 0; sg < 3; sg++)
#pragma unroll
          for (int r = 0; r < 4; r++) {
            uint32_t v = 0;
#pragma unroll
            for (int e = 0; e < 2; e++) {
              const int dlt = (2 * t + e + 8 * (r >> 1) + 16 * (sg - 1)) - (g + 8 * (r & 1));
              v |= (dlt >= lo && dlt <= hi) ? (0x3f80u << (16 * e)) : 0u;
            }
            BA[sg][r] = v;
          }
        uint2 A01[5], A23[5];
#pragma unroll
        for (int s = 0; s < 5; s++) {
          A01[s] = lds64(fb + f * 896 - 32 * (8 + 2 * s));
          A23[s] = lds64(fb + f * 896 - 32 * (7 + 2 * s));
        }
#pragma unroll
        for (int beta = 3; beta >= -1; beta--) {
          float z0[4] = {0.f, 0.f, 0.f, 0.f}, z1[4] = {0.f, 0.f, 0.f, 0.f};
#pragma unroll
          for (int sg = 0; sg < 3; sg++) {
            uint32_t u0, u1, u2, u3;
            ldsm_x4(ur[sg] + beta * 576, u0, u1, u2, u3);
            mma_bf16(z0, BA[sg][0], BA[sg][1], BA[sg][2], BA[sg][3], u0, u1);
            mma_bf16(z1, BA[sg][0], BA[sg][1], BA[sg][2], BA[sg][3], u2, u3);
          }
          const uint32_t b0 = pack_bf16(z0[0], z0[1]), b1 = pack_bf16(z1[0], z1[1]);
          const uint32_t b2 = pack_bf16(z0[2], z0[3]), b3 = pack_bf16(z1[2], z1[3]);
#pragma unroll
          for (int s = 0; s < 5; s++) {
            const int T = beta + 4 + s;
            if (T <= 7) {
              mma_bf16(ac[T - 3][0], A01[s].x, A01[s].y, A23[s].x, A23[s].y, b0, b1);
              mma_bf16(ac[T - 3][1], A01[s].x, A01[s].y, A23[s].x, A23[s].y, b2, b3);
            }
          }
        }
      }
      {
        const uint32_t nk = (uint32_t)__bfloat16_as_ushort(__float2bfloat16_rn(-k1024));
        uint32_t PC[5];
#pragma unroll
        for (int m = 0; m < 5; m++) {
          const int j = 8 * (125 + m) + g - 2 * t;
          PC[m] = ((j == 1020 || j == 1021) ? nk : 0u) | ((j == 1021 || j == 1022) ? (nk << 16) : 0u);
        }
#pragma unroll
        for (int k = 0; k < 2; k++) {
          const uint32_t ab = sbase + SB_U + rowaddr(UZ + 48 - 63 - k + krow) + (lane >> 4) * 16;
#pragma unroll
          for (int T = 3; T <= 7; T++) {
            uint32_t a0, a1, a2, a3;
            ldsm_x4(ab + (T - 3) * 576, a0, a1, a2, a3);
            mma_bf16(ac[T - 3][0], a0, a1, a2, a3, PC[1 + 2 * k], PC[2 * k]);
            mma_bf16(ac[T - 3][1], a0, a1, a2, a3, PC[2 + 2 * k], PC[1 + 2 * k]);
          }
        }
      }
      unsigned char* yb = sm + SB_Y + 16384;
#pragma unroll
      for (int T = 0; T <= 7; T++)
#pragma unroll
        for (int nu = 0; nu < 2; nu++)
#pragma unroll
          for (int hr = 0; hr < 2; hr++)
            *reinterpret_cast<float2*>(yb + ((yl ^ ((8 * (nu ^ hr)) * 4)) + (16 * T + 8 * hr) * 64)) =
                T >= 3 ? make_float2(ac[T >= 3 ? T - 3 : 0][nu][2 * hr], ac[T >= 3 ? T - 3 : 0][nu][2 * hr + 1]) : make_float2(0.f, 0.f);
    }
  }
  if (w < 2) asm volatile("bar.arrive %0, 96;" ::"r"(5 + bar) : "memory");
  named_bar(bar, 128);
  {
    const __nv_bfloat162 ds = *reinterpret_cast<const __nv_bfloat162*>(&dsk2);
    const int r0 = tid >> 2, ch = tid & 3;
    const int yo = (16 * (r0 ^ ((r0 >> 2) & 1)) + ((4 * ch) ^ (8 * (((r0 >> 1) ^ (r0 >> 3)) & 1)))) * 4;
    const int uo = SB_U + rowaddr(r0 + UZ) + ch * 8;
#pragma unroll
    for (int k = 0; k < 4; k++) {
      const float4 a = *reinterpret_cast<const float4*>(sm + SB_Y + yo + k * 2048);
      const float4 b = *reinterpret_cast<const float4*>(sm + SB_Y + 8192 + yo + k * 2048);
      const float4 c = *reinterpret_cast<const float4*>(sm + SB_Y + 16384 + yo + k * 2048);
      const uint2 uw = *reinterpret_cast<const uint2*>(sm + uo + k * 1152);
      const uint2 xw = *reinterpret_cast<const uint2*>(smem_all + FR_X + (sub >> 1) * 8192 + r0 * 64 + (sub & 1) * 32 + ch * 8 + k * 2048);
      const uint32_t y0 = pack_bf16(b.x + (a.x + c.x), b.y + (a.y + c.y)), y1 = pack_bf16(b.z + (a.z + c.z), b.w + (a.w + c.w));
      const __nv_bfloat162 h0 = __hadd2_rn(*reinterpret_cast<const __nv_bfloat162*>(&xw.x),
          __hadd2_rn(*reinterpret_cast<const __nv_bfloat162*>(&y0), __hmul2_rn(*reinterpret_cast<const __nv_bfloat162*>(&uw.x), ds)));
      const __nv_bfloat162 h1 = __hadd2_rn(*reinterpret_cast<const __nv_bfloat162*>(&xw.y),
          __hadd2_rn(*reinterpret_cast<const __nv_bfloat162*>(&y1), __hmul2_rn(*reinterpret_cast<const __nv_bfloat162*>(&uw.y), ds)));
      *reinterpret_cast<uint2*>(g_hT + (size_t)d * SEQ + tid * 4 + k * 512) =
          make_uint2(*reinterpret_cast<const uint32_t*>(&h0), *reinterpret_cast<const uint32_t*>(&h1));
    }
  }
  if (threadIdx.x < 480) {
    asm volatile("bar.arrive 11, 512;" ::: "memory");
  } else {
    fence_async();
    asm volatile("bar.arrive 15, 512;" ::: "memory");
    named_bar(11, 512);
    if (lane == 0) {
      asm volatile("fence.acq_rel.gpu;" ::: "memory");
      asm volatile("red.relaxed.gpu.global.add.u32 [%0], 1;" ::"l"(&g_cnt[blockIdx.x >> 4]) : "memory");
    }
    __syncwarp();
  }
}

constexpr int M_A     = 0;
constexpr int M_W     = 7 * 16384;
constexpr int M_XB    = M_W + 3 * 32768;
constexpr int M_CS    = M_XB + 14336;
constexpr int M_BAR   = M_CS + 1792;
constexpr int M_TOTAL = M_BAR + 384;

template <int NCB, int NA>
__device__ __forceinline__ void g1_pack(const float (&acc)[NA], uint32_t* pk, const float* cs, float mb0, float mb1, int lane) {
  const int t = lane & 3;
#pragma unroll
  for (int cb = 0; cb < NCB; cb++) {
    const float2 sc = *reinterpret_cast<const float2*>(cs + cb * 8 + 2 * t);
    pk[2 * cb]     = pack_bf16(fmaf(-mb0, sc.x, acc[4 * cb + 0]), fmaf(-mb0, sc.y, acc[4 * cb + 1]));
    pk[2 * cb + 1] = pack_bf16(fmaf(-mb1, sc.x, acc[4 * cb + 2]), fmaf(-mb1, sc.y, acc[4 * cb + 3]));
  }
}
__device__ __forceinline__ uint32_t glu2(uint32_t gw, uint32_t uw, float hr) {
  float t0, t1;
  asm("tanh.approx.f32 %0, %1;" : "=f"(t0) : "f"(bflo(gw) * hr));
  asm("tanh.approx.f32 %0, %1;" : "=f"(t1) : "f"(bfhi(gw) * hr));
  return pack_bf16(fmaf(t0, hr, hr) * bflo(uw), fmaf(t1, hr, hr) * bfhi(uw));
}
__device__ __forceinline__ uint32_t w2_slot(int j, int kp) {
  const int sl = j % 10;
  if (sl < 6) return M_W + ((sl >> 1) + 2) % 3 * 32768 + (sl & 1) * 16384;
  const int i = sl - 6;
  return M_A + (i + (i >= kp ? 3 : 0)) * 16384;
}

__global__ void __cluster_dims__(2, 1, 1) __launch_bounds__(512, 1)
k_all(const bf16* __restrict__ Are, const bf16* __restrict__ Aim, const bf16* __restrict__ Bre, const bf16* __restrict__ Bim,
      const bf16* __restrict__ Cre, const bf16* __restrict__ Cim, const bf16* __restrict__ log_dt, const bf16* __restrict__ Dskip,
      const bf16* __restrict__ x, const bf16* __restrict__ wgp, const bf16* __restrict__ wup, const bf16* __restrict__ wdp,
      const __grid_constant__ CUtensorMap tmLu, const __grid_constant__ CUtensorMap tmLx,
      const __grid_constant__ CUtensorMap tmA, const __grid_constant__ CUtensorMap tmG,
      const __grid_constant__ CUtensorMap tmU, const __grid_constant__ CUtensorMap tmD, bf16* __restrict__ out) {
  extern __shared__ __align__(1024) unsigned char smem[];
  const uint32_t sb = smem_u32(smem);
  const int tid = threadIdx.x, lane = tid & 31, warp = tid >> 5;
  const uint32_t barA = sb + M_BAR, barF = barA + 56, barE = barF + 24, barS = barE + 24;
  const uint32_t barW2 = barS + 8, barAf = barW2 + 112, barX = barAf + 8, barH = barX + 8, barE2 = barH + 16;
  if (sb & 1023) __trap();
  if (tid >= 224 && tid < 230) prefetch_tm(tid == 224 ? &tmG : tid == 225 ? &tmU : tid == 226 ? &tmA : tid == 227 ? &tmD : tid == 228 ? &tmLu : &tmLx);
  __syncwarp();

  front_phase(Are, Aim, Bre, Bim, Cre, Cim, log_dt, Dskip, x, wgp, wup, wdp, tmLu, tmLx);

  fence_async();
  if (warp < 15 || blockIdx.x >= 112) named_bar(15, 512);
  const uint32_t rank = blockIdx.x & 1;
  const bool live = blockIdx.x < 128;
  const int pr = live ? blockIdx.x >> 1 : 0;
  const int mt = pr & 15;
  const int fp = pr >> 4;
  const int fj = 4 * rank + fp;
  const int kp = min((112 * fp) >> 6, 4);
  cluster_arrive();

  if (warp >= 8) {
    const unsigned int ep = __ldcg(&g_epoch);
    asm volatile("setmaxnreg.dec.sync.aligned.u32 24;");
    if (!live || warp >= 12) {
      cluster_wait();
      if (warp == 9) { named_bar(2, 288); named_bar(3, 288); }
    } else if (warp == 8) {
      if (lane == 0) {
        for (int it = 0; it < 14; it++) {
          const int s = it % 3, rnd = it / 3;
          const bool pb = it >= 7;
          const int kb = pb ? it - 7 : it;
          if (rnd > 0) mbar_wait(barE + 8 * s, (rnd - 1) & 1);
          mbar_expect(barF + 8 * s, 32768);
          const uint32_t dst = sb + M_W + s * 32768;
          const int c0 = 224 * fj + (pb ? 128 : 0);
          tma2d(dst, &tmG, barF + 8 * s, c0, 64 * kb);
          tma2d(dst + 16384, &tmU, barF + 8 * s, c0, 64 * kb);
          tma2d(dst + 8192, &tmG, barF + 8 * s, c0 + 64, 64 * kb);
          tma2d(dst + 24576, &tmU, barF + 8 * s, c0 + 64, 64 * kb);
        }
        for (int j = 0; j < 14; j++) {
          if (j < 6 && !(j & 1)) { const int it = 11 + (j >> 1); mbar_wait(barE + 8 * (it % 3), (it / 3) & 1); }
          if (j == 6) mbar_wait(barAf, 0);
          if (j >= 10) mbar_wait(barE2 + 8 * (j - 10), 0);
          mbar_expect(barW2 + 8 * j, 16384);
          const uint32_t dst = sb + w2_slot(j, kp);
#pragma unroll
          for (int h = 0; h < 2; h++) {
            const int u = 2 * j + h;
            int c, o;
            if (u < 7) { c = 0; o = u; } else if (u < 19) { c = 1 + (u - 7) / 4; o = (u - 7) % 4; } else { c = 1 + (u - 19) / 3; o = 4 + (u - 19) % 3; }
            const int row = (4 * rank + ((fp + c) & 3)) * 224 + 32 * o;
            tma2d(dst + h * 4096, &tmD, barW2 + 8 * j, 112 * fp, row);
            tma2d(dst + 8192 + h * 4096, &tmD, barW2 + 8 * j, 112 * fp + 64, row);
          }
        }
      }
      __syncwarp();
      cluster_wait();
    } else if (warp == 9) {
      if (lane < 7) flag_wait(&g_cnt[lane], (ep + 1u) * 16u);
      cluster_wait();
      if (lane == 0) {
        asm volatile("fence.proxy.async.global;" ::: "memory");
        for (int k = 0; k < 7; k++) {
          mbar_expect(barA + 8 * k, 16384);
          tma3d_mc(sb + M_A + k * 16384 + rank * 8192, &tmA, barA + 8 * k, 0, 64 * k, 2 * mt + rank, (uint16_t)3);
        }
      }
      __syncwarp();
#pragma unroll 1
      for (int p = 0; p < 2; p++) {
        named_bar(2 + p, 288);
        if (lane == 0) {
          asm volatile("fence.acq_rel.gpu;" ::: "memory");
          asm volatile("red.relaxed.gpu.global.add.u32 [%0], 1;" ::"l"(&g_cnt2[(mt * 2 + rank) * 2 + p]) : "memory");
        }
        __syncwarp();
      }
    } else if (warp == 10) {
      cluster_wait();
      if (lane == 0) {
#pragma unroll 1
        for (int p = 0; p < 2; p++) {
          flag_wait(&g_cnt2[(mt * 2 + rank) * 2 + p], (ep + 1u) * 4u);
          mbar_arrive(barH + 8 * p);
        }
      }
    } else {
      if (lane == 0) flag_wait(&g_cnt[8], (ep + 1u) * 40u);
      __syncwarp();
      float* cs = reinterpret_cast<float*>(smem + M_CS);
      for (int i = lane; i < 448; i += 32) cs[i] = __ldcg(&g_cs[(i >= 224 ? FF + i - 224 : i) + fj * 224]);
      __syncwarp();
      if (lane == 0) mbar_arrive(barS);
      cluster_wait();
    }
    __syncwarp();
    cluster_arrive(); cluster_wait();
  } else {
    asm volatile("setmaxnreg.inc.sync.aligned.u32 232;");
    const int wg = warp >> 2, wq = warp & 3;
    const bool elect = (tid & 127) == 0;
    const float* cs = reinterpret_cast<const float*>(smem + M_CS);
#define RELEASE(b) do { if (elect) mbar_arrive(b); } while (0)
#define PUBLISH(p) asm volatile("bar.arrive %0, 288;" ::"r"(2 + (p)) : "memory")
    const int dr = (lane & 7) + 8 * (lane >> 4), tc = 2 * wq + ((lane >> 3) & 1);
    const uint32_t aT = sb + M_A + wg * 8192 + dr * 128 + ((tc ^ (lane & 7)) << 4);
    uint4* hbase = reinterpret_cast<uint4*>(g_P) + (size_t)(mt * 8 * 8 + warp) * (14 * 32) + lane;
    const uint32_t dead = live ? 0u : 1u;
    float mb0, rs0, mb1, rs1;
    uint32_t pkA[64];
    {
      float accA[64], accB[64];
      float s0 = 0.f, q0 = 0.f, s1 = 0.f, q1 = 0.f;
#pragma unroll
      for (int kb = 0; kb < 7; kb++) {
        const int s = kb % 3;
        mbar_wait(barA + 8 * kb, (0) | dead);
        uint32_t af[4][4];
#pragma unroll
        for (int k = 0; k < 4; k++) ldsm_x4_t(aT + kb * 16384 + k * 2048, af[k][0], af[k][1], af[k][2], af[k][3]);
        mbar_wait(barF + 8 * s, ((kb / 3) & 1) | dead);
        const uint64_t db = mk_desc(sb + M_W + s * 32768, 8192, 1024, 1);
        wg_fence();
#pragma unroll
        for (int k = 0; k < 4; k++) {
          wgmma_rs_n128(accA, af[k][0], af[k][1], af[k][2], af[k][3], db + k * 128, (kb | k) != 0);
          wgmma_rs_n128(accB, af[k][0], af[k][1], af[k][2], af[k][3], db + 1024 + k * 128, (kb | k) != 0);
        }
        wg_commit();
        if (kb > 0) { wg_wait<1>(); RELEASE(barE + 8 * ((kb - 1) % 3)); }
#pragma unroll
        for (int k = 0; k < 4; k++) {
#pragma unroll
          for (int h = 0; h < 2; h++) {
            const float a = bflo(af[k][2 * h]), b = bfhi(af[k][2 * h]), c = bflo(af[k][2 * h + 1]), e = bfhi(af[k][2 * h + 1]);
            s0 += a + b; q0 = fmaf(a, a, fmaf(b, b, q0));
            s1 += c + e; q1 = fmaf(c, c, fmaf(e, e, q1));
          }
        }
      }
#pragma unroll
      for (int o = 1; o <= 2; o <<= 1) {
        s0 += __shfl_xor_sync(0xffffffffu, s0, o); q0 += __shfl_xor_sync(0xffffffffu, q0, o);
        s1 += __shfl_xor_sync(0xffffffffu, s1, o); q1 += __shfl_xor_sync(0xffffffffu, q1, o);
      }
      s0 *= (1.0f / DM); s1 *= (1.0f / DM);
      mb0 = bf16r(s0); mb1 = bf16r(s1);
      rs0 = 0.5f * ln_rden(fmaxf(q0 * (1.0f / DM) - s0 * s0, 0.f));
      rs1 = 0.5f * ln_rden(fmaxf(q1 * (1.0f / DM) - s1 * s1, 0.f));
      mbar_wait(barS, (0) | dead);
      wg_wait<0>();
      RELEASE(barE + 0);
      g1_pack<16, 64>(accA, pkA, cs, mb0, mb1, lane);
      g1_pack<16, 64>(accB, pkA + 32, cs + 224, mb0, mb1, lane);
    }
    uint32_t hf[56];
    uint4* hown = live ? hbase + (size_t)fj * (8 * 14 * 32) : reinterpret_cast<uint4*>(g_dummy) + lane;
    {
      float accG[48], accU[48];
#pragma unroll
      for (int kb = 0; kb < 7; kb++) {
        const int it = kb + 7, s = it % 3;
        uint32_t af[4][4];
#pragma unroll
        for (int k = 0; k < 4; k++) ldsm_x4_t(aT + kb * 16384 + k * 2048, af[k][0], af[k][1], af[k][2], af[k][3]);
        mbar_wait(barF + 8 * s, ((it / 3) & 1) | dead);
        const uint64_t db = mk_desc(sb + M_W + s * 32768, 8192, 1024, 1);
        wg_fence();
#pragma unroll
        for (int k = 0; k < 4; k++) {
          wgmma_rs_n96(accG, af[k][0], af[k][1], af[k][2], af[k][3], db + k * 128, (kb | k) != 0);
          wgmma_rs_n96(accU, af[k][0], af[k][1], af[k][2], af[k][3], db + 1024 + k * 128, (kb | k) != 0);
        }
        wg_commit();
        if (kb > 0) { wg_wait<1>(); RELEASE(barE + 8 * ((it - 1) % 3)); }
        if (kb < 4) {
#pragma unroll
          for (int i = 0; i < 8; i++) hf[8 * kb + i] = glu2(pkA[8 * kb + i], pkA[32 + 8 * kb + i], (i & 1) ? rs1 : rs0);
          hown[(2 * kb) * 32] = make_uint4(hf[8 * kb], hf[8 * kb + 1], hf[8 * kb + 2], hf[8 * kb + 3]);
          hown[(2 * kb + 1) * 32] = make_uint4(hf[8 * kb + 4], hf[8 * kb + 5], hf[8 * kb + 6], hf[8 * kb + 7]);
          if (kb == 3) PUBLISH(0);
        }
      }
      wg_wait<0>();
      if (elect) { mbar_arrive(barE + 8 * (13 % 3)); mbar_arrive(barAf); }
#pragma unroll
      for (int cb = 0; cb < 12; cb++) {
        const float2 sg = *reinterpret_cast<const float2*>(cs + 128 + cb * 8 + 2 * (lane & 3));
        const float2 su = *reinterpret_cast<const float2*>(cs + 352 + cb * 8 + 2 * (lane & 3));
#pragma unroll
        for (int h = 0; h < 2; h++) {
          const float mb = h ? mb1 : mb0, hr = h ? rs1 : rs0;
          float t0, t1;
          asm("tanh.approx.f32 %0, %1;" : "=f"(t0) : "f"(fmaf(-mb, sg.x, accG[4 * cb + 2 * h]) * hr));
          asm("tanh.approx.f32 %0, %1;" : "=f"(t1) : "f"(fmaf(-mb, sg.y, accG[4 * cb + 2 * h + 1]) * hr));
          hf[32 + 2 * cb + h] = pack_bf16(fmaf(t0, hr, hr) * fmaf(-mb, su.x, accU[4 * cb + 2 * h]), fmaf(t1, hr, hr) * fmaf(-mb, su.y, accU[4 * cb + 2 * h + 1]));
        }
      }
    }
#pragma unroll
    for (int q = 0; q < 6; q++) hown[(8 + q) * 32] = make_uint4(hf[32 + 4 * q], hf[33 + 4 * q], hf[34 + 4 * q], hf[35 + 4 * q]);
    PUBLISH(1);
    float acc[56];
    auto hsrc = [&](int i) -> const uint4* {
      int c, o;
      if (i < 38) { c = 1 + (i - 14) / 8; o = (i - 14) % 8; } else { c = 1 + (i - 38) / 6; o = 8 + (i - 38) % 6; }
      return hbase + (size_t)(4 * rank + ((fp + c) & 3)) * (8 * 14 * 32) + o * 32;
    };
    uint4 hq[4][4];
#pragma unroll
    for (int j = 0; j < 14; j++) {
      if (j == 1) mbar_wait(barH, dead);
      if (j == 7) mbar_wait(barH + 8, dead);
#pragma unroll
      for (int k = 0; k < 4; k++) {
        const int i = 4 * (j + 2) + k;
        if (i >= 14 && i < 56) hq[(j + 2) & 3][k] = __ldcg(hsrc(i));
      }
      mbar_wait(barW2 + 8 * j, (0) | dead);
      const uint64_t db = mk_desc(sb + w2_slot(j, kp), 8192, 1024, 1);
      wg_fence();
#pragma unroll
      for (int k = 0; k < 4; k++) {
        const int i = 4 * j + k;
        if (i < 14) wgmma_rs_n112(acc, hf[4 * i], hf[4 * i + 1], hf[4 * i + 2], hf[4 * i + 3], db + k * 128, i != 0);
        else wgmma_rs_n112(acc, hq[j & 3][k].x, hq[j & 3][k].y, hq[j & 3][k].z, hq[j & 3][k].w, db + k * 128, 1);
      }
      wg_commit();
      if (j > 0) { wg_wait<1>(); if (j <= 4) RELEASE(barE2 + 8 * (j - 1)); }
    }
    wg_wait<0>();
    cluster_wait();
    if (wg != (int)rank) {
      asm volatile("bar.arrive 1, 256;" ::: "memory");
      const uint32_t xd = mapa(sb + M_XB, rank ^ 1) + (tid & 127) * 16;
      const uint32_t xb = mapa(barX, rank ^ 1);
#pragma unroll
      for (int q = 0; q < 7; q++)
        asm volatile("st.async.weak.shared::cluster.mbarrier::complete_tx::bytes.v4.b32 [%0], {%1,%2,%3,%4}, [%5];"
                     ::"r"(xd + q * 2048), "r"(pack_bf16(acc[8 * q], acc[8 * q + 1])), "r"(pack_bf16(acc[8 * q + 2], acc[8 * q + 3])),
                       "r"(pack_bf16(acc[8 * q + 4], acc[8 * q + 5])), "r"(pack_bf16(acc[8 * q + 6], acc[8 * q + 7])), "r"(xb) : "memory");
    } else {
      uint32_t hr[7][4];
      const int d0 = 112 * fp;
#pragma unroll
      for (int q = 0; q < 7; q++) {
        const int dd = d0 + 16 * q;
        ldsm_x4_t(aT + (dd >> 6) * 16384 + (dd & 63) * 128, hr[q][0], hr[q][1], hr[q][2], hr[q][3]);
      }
      if (elect) mbar_expect(barX, 14336);
      mbar_wait(barX, 0);
      const uint32_t stg = sb + M_W + wq * 3840;
      const uint32_t so = stg + ((lane & 7) + 8 * ((lane >> 3) & 1)) * 240 + (lane >> 4) * 16;
      named_bar(1, 256);
#pragma unroll
      for (int q = 0; q < 7; q++) {
        const uint4 v = *reinterpret_cast<const uint4*>(smem + M_XB + q * 2048 + (tid & 127) * 16);
        const uint32_t m0 = pack_bf16(acc[8 * q] + bflo(v.x), acc[8 * q + 1] + bfhi(v.x)), m1 = pack_bf16(acc[8 * q + 2] + bflo(v.y), acc[8 * q + 3] + bfhi(v.y));
        const uint32_t m2 = pack_bf16(acc[8 * q + 4] + bflo(v.z), acc[8 * q + 5] + bfhi(v.z)), m3 = pack_bf16(acc[8 * q + 6] + bflo(v.w), acc[8 * q + 7] + bfhi(v.w));
        stsm_x4(so + q * 32, hadd2_bf16(hr[q][0], m0), hadd2_bf16(hr[q][1], m1), hadd2_bf16(hr[q][2], m2), hadd2_bf16(hr[q][3], m3));
      }
      __syncwarp();
      bf16* o = live ? out + (size_t)(mt * 128 + 64 * wg + 16 * wq) * DM + d0 : g_dummy;
#pragma unroll
      for (int k = 0; k < 7; k++) {
        const int c = lane + 32 * k;
        const int r = c / 14, ch = c - 14 * r;
        *reinterpret_cast<uint4*>(o + (size_t)r * DM + ch * 8) = *reinterpret_cast<const uint4*>(smem + M_W + wq * 3840 + r * 240 + ch * 16);
      }
    }
    if (tid == 0 && live) {
      const unsigned int n = atomicAdd(&g_done, 1u);
      if ((n & 127u) == 127u) atomicAdd(&g_epoch, 1u);
    }
    __syncwarp();
    cluster_arrive(); cluster_wait();
#undef PUBLISH
#undef RELEASE
  }
}

typedef CUresult (*EncFn)(CUtensorMap*, CUtensorMapDataType, cuuint32_t, void*, const cuuint64_t*, const cuuint64_t*,
                          const cuuint32_t*, const cuuint32_t*, CUtensorMapInterleave, CUtensorMapSwizzle,
                          CUtensorMapL2promotion, CUtensorMapFloatOOBfill);

static void make_map(EncFn enc, CUtensorMap* tm, const void* ptr, int rank, const uint64_t* dims, const uint64_t* strides_bytes,
                     const uint32_t* box, CUtensorMapSwizzle swz) {
  cuuint64_t gd[3], gs[2]; cuuint32_t bd[3], es[3] = {1, 1, 1};
  for (int i = 0; i < rank; i++) { gd[i] = dims[i]; bd[i] = box[i]; }
  for (int i = 0; i < rank - 1; i++) gs[i] = strides_bytes[i];
  enc(tm, CU_TENSOR_MAP_DATA_TYPE_BFLOAT16, rank, const_cast<void*>(ptr), gd, gs, bd, es, CU_TENSOR_MAP_INTERLEAVE_NONE, swz,
      CU_TENSOR_MAP_L2_PROMOTION_L2_128B, CU_TENSOR_MAP_FLOAT_OOB_FILL_NONE);
}

template <class K, class... Args>
static void launch_k(K kern, int grid, int block, int smem, bool pdl, Args... args) {
  cudaLaunchConfig_t cfg = {};
  cfg.gridDim = dim3(grid); cfg.blockDim = dim3(block); cfg.dynamicSmemBytes = smem; cfg.stream = cudaStreamPerThread;
  cudaLaunchAttribute at[1];
  at[0].id = cudaLaunchAttributeProgrammaticStreamSerialization;
  at[0].val.programmaticStreamSerializationAllowed = 1;
  cfg.attrs = at; cfg.numAttrs = pdl ? 1 : 0;
  cudaLaunchKernelEx(&cfg, kern, args...);
}

extern "C" void kernel_launch(void* const* d_in, const int* in_sizes, int n_in, void* d_out, int out_size) {
  const bf16* x   = (const bf16*)d_in[0];
  const bf16* Are = (const bf16*)d_in[1];
  const bf16* Aim = (const bf16*)d_in[2];
  const bf16* Bre = (const bf16*)d_in[3];
  const bf16* Bim = (const bf16*)d_in[4];
  const bf16* Cre = (const bf16*)d_in[5];
  const bf16* Cim = (const bf16*)d_in[6];
  const bf16* ldt = (const bf16*)d_in[7];
  const bf16* dsk = (const bf16*)d_in[8];
  const bf16* wg  = (const bf16*)d_in[10];
  const bf16* wu  = (const bf16*)d_in[11];
  const bf16* wd  = (const bf16*)d_in[12];

  static EncFn enc = nullptr;
  static void *p_hT = nullptr, *p_uT = nullptr, *p_xT = nullptr;
  if (!enc) {
    void* fn = nullptr; cudaDriverEntryPointQueryResult qr;
    cudaGetDriverEntryPoint("cuTensorMapEncodeTiled", &fn, cudaEnableDefault, &qr);
    enc = (EncFn)fn;
    cudaGetSymbolAddress(&p_hT, g_hT);
    cudaGetSymbolAddress(&p_uT, g_uT);
    cudaGetSymbolAddress(&p_xT, g_xT);
    cudaFuncSetAttribute(k_all, cudaFuncAttributeMaxDynamicSharedMemorySize, M_TOTAL);
  }
  CUtensorMap tmA, tmG, tmU, tmD, tmLu, tmLx;
  {
    uint64_t dims[2] = {DM * 16, SEQ / 16}, st[1] = {DM * 32};
    uint32_t box[2] = {32, 128};
    make_map(enc, &tmLu, p_uT, 2, dims, st, box, CU_TENSOR_MAP_SWIZZLE_NONE);
    make_map(enc, &tmLx, p_xT, 2, dims, st, box, CU_TENSOR_MAP_SWIZZLE_NONE);
  }
  {
    uint64_t dims[3] = {64, DM, SEQ / 64}, st[2] = {SEQ * 2, 128};
    uint32_t box[3] = {64, 64, 1};
    make_map(enc, &tmA, p_hT, 3, dims, st, box, CU_TENSOR_MAP_SWIZZLE_128B);
  }
  {
    uint64_t dims[2] = {FF, DM}, st[1] = {FF * 2};
    uint32_t box[2] = {64, 64};
    make_map(enc, &tmG, wg, 2, dims, st, box, CU_TENSOR_MAP_SWIZZLE_128B);
    make_map(enc, &tmU, wu, 2, dims, st, box, CU_TENSOR_MAP_SWIZZLE_128B);
  }
  {
    uint64_t dims[2] = {DM, FF}, st[1] = {DM * 2};
    uint32_t box[2] = {64, 32};
    make_map(enc, &tmD, wd, 2, dims, st, box, CU_TENSOR_MAP_SWIZZLE_128B);
  }
  static_assert(FR_BAR == M_BAR + 320 && FR_BAR + 16 <= M_TOTAL, "barrier placement");
  static_assert(FRONT_SMEM <= M_XB, "front phase must not touch the MLP barriers");
  launch_k(k_all, 132, 512, M_TOTAL, false, Are, Aim, Bre, Bim, Cre, Cim, ldt, dsk, x, wg, wu, wd, tmLu, tmLx, tmA, tmG, tmU, tmD, (bf16*)d_out);
}
```

```cpp
#include <cuda_runtime.h>
#include <cuda_bf16.h>
#include <cuda_fp16.h>
#include <cuda.h>
#include <stdint.h>

typedef __nv_bfloat16 bf16;

constexpr int SEQ = 2048;
constexpr int DM  = 448;
constexpr int NM  = 256;
constexpr int FF  = 1792;

__device__ __align__(1024) bf16  g_uT[DM * SEQ];
__device__ __align__(1024) bf16  g_xT[DM * SEQ];
__device__ __align__(1024) bf16  g_hT[DM * SEQ];
__device__ __align__(1024) bf16  g_P[SEQ * FF];
__device__ __align__(1024) bf16  g_dummy[16 * DM];
__device__ __align__(1024) float g_cs[2 * FF];

__device__ __forceinline__ uint32_t smem_u32(const void* p) { return (uint32_t)__cvta_generic_to_shared(p); }
__device__ __forceinline__ float bf16r(float v) { return __bfloat162float(__float2bfloat16_rn(v)); }
__device__ __forceinline__ float bflo(uint32_t w) { return __uint_as_float(w << 16); }
__device__ __forceinline__ float bfhi(uint32_t w) { return __uint_as_float(w & 0xffff0000u); }
__device__ __forceinline__ uint32_t pack_bf16(float lo, float hi) {
  uint32_t r; asm("cvt.rn.bf16x2.f32 %0, %1, %2;" : "=r"(r) : "f"(hi), "f"(lo)); return r;
}
__device__ __forceinline__ uint32_t pack_f16(float lo, float hi) {
  uint32_t r; asm("cvt.rn.f16x2.f32 %0, %1, %2;" : "=r"(r) : "f"(hi), "f"(lo)); return r;
}
__device__ __forceinline__ float ex2f(float x) { float r; asm("ex2.approx.ftz.f32 %0, %1;" : "=f"(r) : "f"(x)); return r; }
__device__ __forceinline__ float ln_rden(float var) {
  float sq, r;
  asm("sqrt.approx.ftz.f32 %0, %1;" : "=f"(sq) : "f"(bf16r(bf16r(var) + 1e-5f)));
  asm("rcp.approx.ftz.f32 %0, %1;" : "=f"(r) : "f"(bf16r(sq)));
  return r;
}
__device__ __forceinline__ uint32_t hadd2_bf16(uint32_t a, uint32_t b) {
  const __nv_bfloat162 r = __hadd2_rn(*reinterpret_cast<const __nv_bfloat162*>(&a), *reinterpret_cast<const __nv_bfloat162*>(&b));
  return *reinterpret_cast<const uint32_t*>(&r);
}
__device__ __forceinline__ void pdl_launch() { asm volatile("griddepcontrol.launch_dependents;"); }
__device__ __forceinline__ void pdl_wait() { asm volatile("griddepcontrol.wait;" ::: "memory"); }

__device__ __forceinline__ void mbar_init(uint32_t a, int c) { asm volatile("mbarrier.init.shared::cta.b64 [%0], %1;" ::"r"(a), "r"(c)); }
__device__ __forceinline__ void mbar_expect(uint32_t a, uint32_t bytes) {
  asm volatile("mbarrier.arrive.expect_tx.shared::cta.b64 _, [%0], %1;" ::"r"(a), "r"(bytes) : "memory");
}
__device__ __forceinline__ void mbar_arrive(uint32_t a) { asm volatile("mbarrier.arrive.shared::cta.b64 _, [%0];" ::"r"(a) : "memory"); }
__device__ __forceinline__ void mbar_arrive_cluster(uint32_t remote_a) {
  asm volatile("mbarrier.arrive.shared::cluster.b64 _, [%0];" ::"r"(remote_a) : "memory");
}
__device__ __forceinline__ void mbar_wait(uint32_t a, uint32_t ph) {
  uint32_t ok; int it = 0;
  do {
    asm volatile("{.reg .pred p; mbarrier.try_wait.parity.shared::cta.b64 p, [%1], %2; selp.u32 %0,1,0,p;}"
                 : "=r"(ok) : "r"(a), "r"(ph) : "memory");
  } while (!ok && ++it < (1 << 24));
}
__device__ __forceinline__ void flag_wait(const unsigned int* p, unsigned int target) {
  unsigned int v; int it = 0;
  asm volatile("ld.acquire.gpu.global.u32 %0, [%1];" : "=r"(v) : "l"(p) : "memory");
  if ((int)(v - target) >= 0) return;
  while (true) {
    __nanosleep(32);
    asm volatile("ld.relaxed.gpu.global.u32 %0, [%1];" : "=r"(v) : "l"(p) : "memory");
    if ((int)(v - target) >= 0 || ++it > (1 << 22)) break;
  }
  asm volatile("ld.acquire.gpu.global.u32 %0, [%1];" : "=r"(v) : "l"(p) : "memory");
}
__device__ __forceinline__ uint4 ld_relaxed_v4(const uint4* p) {
  uint4 v; asm volatile("ld.relaxed.gpu.global.v4.u32 {%0,%1,%2,%3}, [%4];" : "=r"(v.x), "=r"(v.y), "=r"(v.z), "=r"(v.w) : "l"(p) : "memory"); return v;
}
__device__ __forceinline__ void st_relaxed_v4(uint4* p, uint32_t a, uint32_t b, uint32_t c, uint32_t d) {
  asm volatile("st.relaxed.gpu.global.v4.u32 [%0], {%1,%2,%3,%4};" ::"l"(p), "r"(a), "r"(b), "r"(c), "r"(d) : "memory");
}
__device__ __forceinline__ uint32_t mapa(uint32_t a, uint32_t rank) {
  uint32_t r; asm volatile("mapa.shared::cluster.u32 %0, %1, %2;" : "=r"(r) : "r"(a), "r"(rank)); return r;
}
__device__ __forceinline__ void cluster_arrive() { asm volatile("barrier.cluster.arrive.relaxed.aligned;" ::: "memory"); }
__device__ __forceinline__ void cluster_wait() { asm volatile("barrier.cluster.wait.acquire.aligned;" ::: "memory"); }
__device__ __forceinline__ void fence_async() { asm volatile("fence.proxy.async.shared::cta;" ::: "memory"); }
__device__ __forceinline__ void named_bar(int id, int n) { asm volatile("bar.sync %0, %1;" ::"r"(id), "r"(n) : "memory"); }

__device__ __forceinline__ void tma2d(uint32_t dst, const CUtensorMap* tm, uint32_t bar, int c0, int c1) {
  asm volatile("cp.async.bulk.tensor.2d.shared::cluster.global.mbarrier::complete_tx::bytes [%0], [%1, {%3,%4}], [%2];"
               ::"r"(dst), "l"(tm), "r"(bar), "r"(c0), "r"(c1) : "memory");
}
__device__ __forceinline__ void tma3d(uint32_t dst, const CUtensorMap* tm, uint32_t bar, int c0, int c1, int c2) {
  asm volatile("cp.async.bulk.tensor.3d.shared::cluster.global.mbarrier::complete_tx::bytes [%0], [%1, {%3,%4,%5}], [%2];"
               ::"r"(dst), "l"(tm), "r"(bar), "r"(c0), "r"(c1), "r"(c2) : "memory");
}
__device__ __forceinline__ void tma3d_mc(uint32_t dst, const CUtensorMap* tm, uint32_t bar, int c0, int c1, int c2, uint16_t mask) {
  asm volatile("cp.async.bulk.tensor.3d.shared::cluster.global.mbarrier::complete_tx::bytes.multicast::cluster [%0], [%1, {%3,%4,%5}], [%2], %6;"
               ::"r"(dst), "l"(tm), "r"(bar), "r"(c0), "r"(c1), "r"(c2), "h"(mask) : "memory");
}
__device__ __forceinline__ void tma2d_store(const CUtensorMap* tm, uint32_t src, int c0, int c1) {
  asm volatile("cp.async.bulk.tensor.2d.global.shared::cta.bulk_group [%0, {%2,%3}], [%1];"
               ::"l"(tm), "r"(src), "r"(c0), "r"(c1) : "memory");
}
__device__ __forceinline__ void bulk_commit() { asm volatile("cp.async.bulk.commit_group;" ::: "memory"); }
template <int N> __device__ __forceinline__ void bulk_wait_read() { asm volatile("cp.async.bulk.wait_group.read %0;" ::"n"(N) : "memory"); }
template <int N> __device__ __forceinline__ void bulk_wait() { asm volatile("cp.async.bulk.wait_group %0;" ::"n"(N) : "memory"); }
__device__ __forceinline__ void prefetch_tm(const CUtensorMap* tm) { asm volatile("prefetch.tensormap [%0];" ::"l"(tm) : "memory"); }

__device__ __forceinline__ void wg_fence() { asm volatile("wgmma.fence.sync.aligned;" ::: "memory"); }
__device__ __forceinline__ void wg_commit() { asm volatile("wgmma.commit_group.sync.aligned;" ::: "memory"); }
template <int N> __device__ __forceinline__ void wg_wait() { asm volatile("wgmma.wait_group.sync.aligned %0;" ::"n"(N) : "memory"); }
__device__ __forceinline__ uint64_t mk_desc(uint32_t addr, uint32_t lbo, uint32_t sbo, uint32_t swz) {
  return (uint64_t)((addr & 0x3FFFF) >> 4) | ((uint64_t)(lbo >> 4) << 16) | ((uint64_t)(sbo >> 4) << 32) | ((uint64_t)swz << 62);
}
__device__ __forceinline__ void ldsm_x4(uint32_t a, uint32_t& r0, uint32_t& r1, uint32_t& r2, uint32_t& r3) {
  asm volatile("ldmatrix.sync.aligned.m8n8.x4.shared.b16 {%0,%1,%2,%3}, [%4];" : "=r"(r0), "=r"(r1), "=r"(r2), "=r"(r3) : "r"(a));
}
__device__ __forceinline__ void ldsm_x4_t(uint32_t a, uint32_t& r0, uint32_t& r1, uint32_t& r2, uint32_t& r3) {
  asm volatile("ldmatrix.sync.aligned.m8n8.x4.trans.shared.b16 {%0,%1,%2,%3}, [%4];" : "=r"(r0), "=r"(r1), "=r"(r2), "=r"(r3) : "r"(a));
}
__device__ __forceinline__ void ldsm_x2_t(uint32_t a, uint32_t& r0, uint32_t& r1) {
  asm volatile("ldmatrix.sync.aligned.m8n8.x2.trans.shared.b16 {%0,%1}, [%2];" : "=r"(r0), "=r"(r1) : "r"(a));
}
__device__ __forceinline__ void stsm_x4(uint32_t a, uint32_t r0, uint32_t r1, uint32_t r2, uint32_t r3) {
  asm volatile("stmatrix.sync.aligned.m8n8.x4.shared.b16 [%0], {%1,%2,%3,%4};" ::"r"(a), "r"(r0), "r"(r1), "r"(r2), "r"(r3) : "memory");
}
__device__ __forceinline__ void stsm_x2(uint32_t a, uint32_t r0, uint32_t r1) {
  asm volatile("stmatrix.sync.aligned.m8n8.x2.shared.b16 [%0], {%1,%2};" ::"r"(a), "r"(r0), "r"(r1) : "memory");
}
__device__ __forceinline__ uint32_t lds32(uint32_t a) { uint32_t r; asm volatile("ld.shared.u32 %0, [%1];" : "=r"(r) : "r"(a)); return r; }
__device__ __forceinline__ void mma_bf16(float (&c)[4], uint32_t a0, uint32_t a1, uint32_t a2, uint32_t a3, uint32_t b0, uint32_t b1) {
  asm volatile("mma.sync.aligned.m16n8k16.row.col.f32.bf16.bf16.f32 {%0,%1,%2,%3}, {%4,%5,%6,%7}, {%8,%9}, {%0,%1,%2,%3};"
               : "+f"(c[0]), "+f"(c[1]), "+f"(c[2]), "+f"(c[3]) : "r"(a0), "r"(a1), "r"(a2), "r"(a3), "r"(b0), "r"(b1));
}
__device__ __forceinline__ void mma_f16(float (&c)[4], uint32_t a0, uint32_t a1, uint32_t a2, uint32_t a3, uint32_t b0, uint32_t b1) {
  asm volatile("mma.sync.aligned.m16n8k16.row.col.f32.f16.f16.f32 {%0,%1,%2,%3}, {%4,%5,%6,%7}, {%8,%9}, {%0,%1,%2,%3};"
               : "+f"(c[0]), "+f"(c[1]), "+f"(c[2]), "+f"(c[3]) : "r"(a0), "r"(a1), "r"(a2), "r"(a3), "r"(b0), "r"(b1));
}
__device__ __forceinline__ void cp_async16(uint32_t dst, const void* src) {
  asm volatile("cp.async.cg.shared.global [%0], [%1], 16;" ::"r"(dst), "l"(src) : "memory");
}
__device__ __forceinline__ void cp_async_wait_all() { asm volatile("cp.async.wait_all;" ::: "memory"); }

__device__ unsigned int g_epoch;
__device__ unsigned int g_cnt[16];
__device__ unsigned int g_cnt2[256];
__device__ unsigned int g_done;

constexpr int LN_PITCH = 912;
constexpr int LN_STAT  = 16 * LN_PITCH;
constexpr int LN_SMEM  = LN_STAT + 7 * 128;
__device__ __forceinline__ void ln1_load(const bf16* __restrict__ x, int tile, unsigned char* sm) {
  const int r = (threadIdx.x >> 4) & 15, c = threadIdx.x & 15;
  const uint32_t dst = smem_u32(sm) + r * LN_PITCH + c * 16;
  const bf16* src = x + (size_t)(tile * 16 + r) * DM + c * 8;
#pragma unroll
  for (int k = 0; k < 4; k++)
    if (k < 3 || c < 8) cp_async16(dst + k * 256, src + k * 128);
}
__device__ __forceinline__ void ln1_tile(int tile, unsigned char* sm) {
  const uint32_t sb = smem_u32(sm);
  const int lane = threadIdx.x & 31, w = (threadIdx.x >> 5) - 8;
  const int g = lane >> 2, t = lane & 3;
  cp_async_wait_all();
  named_bar(14, 256);
  if (w < 7) {
    float s1[4] = {0.f, 0.f, 0.f, 0.f}, qa[4] = {0.f, 0.f, 0.f, 0.f}, qb[4] = {0.f, 0.f, 0.f, 0.f};
    const uint32_t ad = sb + ((lane & 7) + 8 * ((lane >> 3) & 1)) * LN_PITCH + (lane >> 4) * 16 + w * 128;
#pragma unroll
    for (int k = 0; k < 4; k++) {
      uint32_t a0, a1, a2, a3;
      ldsm_x4(ad + k * 32, a0, a1, a2, a3);
      mma_bf16(s1, a0, a1, a2, a3, 0x3f803f80u, 0x3f803f80u);
      mma_bf16(qa, a0, a1, a2, a3, a0, a2);
      mma_bf16(qb, a0, a1, a2, a3, a1, a3);
    }
    if (t == (g >> 1)) {
      float2* st = reinterpret_cast<float2*>(sm + LN_STAT) + w * 16;
      st[g]     = make_float2(s1[0], (g & 1) ? qa[1] : qa[0]);
      st[g + 8] = make_float2(s1[2], (g & 1) ? qb[3] : qb[2]);
    }
  }
  named_bar(14, 256);
  if (w < 7) {
    float mb[4], rd[4];
    {
      const float2* st = reinterpret_cast<const float2*>(sm + LN_STAT) + (lane & 15);
      float sx = 0.f, sy = 0.f;
#pragma unroll
      for (int i = 0; i < 7; i++) { const float2 p = st[16 * i]; sx += p.x; sy += p.y; }
      const float mean = sx * (1.0f / DM);
      const float var = fmaxf(sy * (1.0f / DM) - mean * mean, 0.f);
      const float m = bf16r(mean);
      const float r = ln_rden(var);
#pragma unroll
      for (int e = 0; e < 4; e++) {
        mb[e] = __shfl_sync(0xffffffffu, m, 4 * t + e);
        rd[e] = __shfl_sync(0xffffffffu, r, 4 * t + e);
      }
    }
    const int r8 = lane & 7;
    const int tok = 4 * (r8 >> 1) + (r8 & 1) + 2 * ((lane >> 3) & 1);
    const uint32_t ad = sb + tok * LN_PITCH + (w * 64 + (lane >> 4) * 8) * 2;
    const size_t go = (size_t)(tile * DM + w * 64 + g) * 16 + 4 * t;
#pragma unroll
    for (int k = 0; k < 4; k++) {
      uint32_t v[4];
      ldsm_x4_t(ad + k * 32, v[0], v[1], v[2], v[3]);
#pragma unroll
      for (int h = 0; h < 2; h++) {
        const uint32_t d0 = pack_bf16(bflo(v[2 * h]) - mb[0], bfhi(v[2 * h]) - mb[1]);
        const uint32_t d1 = pack_bf16(bflo(v[2 * h + 1]) - mb[2], bfhi(v[2 * h + 1]) - mb[3]);
        const size_t o = go + (size_t)(16 * k + 8 * h) * 16;
        *reinterpret_cast<uint2*>(g_uT + o) = make_uint2(pack_bf16(bflo(d0) * rd[0], bfhi(d0) * rd[1]), pack_bf16(bflo(d1) * rd[2], bfhi(d1) * rd[3]));
        *reinterpret_cast<uint2*>(g_xT + o) = make_uint2(v[2 * h], v[2 * h + 1]);
      }
    }
    asm volatile("bar.arrive 12, 256;" ::: "memory");
  } else {
    named_bar(12, 256);
    if (lane == 0) {
      asm volatile("fence.acq_rel.gpu;" ::: "memory");
      asm volatile("red.relaxed.gpu.global.add.u32 [%0], 1;" ::"l"(&g_cnt[7]) : "memory");
    }
    __syncwarp();
  }
}

constexpr int CS_SMEM = 448 * 64 + 16 * 128;
__device__ __forceinline__ void colsum_load(const bf16* __restrict__ wg, const bf16* __restrict__ wu, int b2, unsigned char* sm) {
  const bf16* W = (b2 >= 56 ? wu : wg) + (b2 % 56) * 32;
  const uint32_t sb = smem_u32(sm);
#pragma unroll
  for (int k = 0; k < 7; k++)
    cp_async16(sb + (threadIdx.x & 255) * 16 + k * 4096, W + (size_t)((threadIdx.x & 255) >> 2) * FF + (threadIdx.x & 3) * 8 + (size_t)k * 64 * FF);
}
__device__ __forceinline__ void colsum_reduce(unsigned char* sm) {
  const int lane = threadIdx.x & 31, w = (threadIdx.x >> 5) & 7;
  if (w >= 7) return;
  float acc[4][4];
#pragma unroll
  for (int i = 0; i < 4; i++) { acc[i][0] = acc[i][1] = acc[i][2] = acc[i][3] = 0.f; }
  const uint32_t ad = smem_u32(sm) + (w * 64 + (lane & 15)) * 64 + (lane >> 4) * 16;
#pragma unroll
  for (int k = 0; k < 4; k++) {
#pragma unroll
    for (int h = 0; h < 2; h++) {
      uint32_t b0, b1, b2, b3;
      ldsm_x4_t(ad + k * 1024 + h * 32, b0, b1, b2, b3);
      mma_bf16(acc[2 * h], 0x3f803f80u, 0x3f803f80u, 0x3f803f80u, 0x3f803f80u, b0, b1);
      mma_bf16(acc[2 * h + 1], 0x3f803f80u, 0x3f803f80u, 0x3f803f80u, 0x3f803f80u, b2, b3);
    }
  }
  if (lane < 4) {
    float* sf = reinterpret_cast<float*>(sm + 448 * 64) + w * 32 + 2 * lane;
#pragma unroll
    for (int i = 0; i < 4; i++) *reinterpret_cast<float2*>(sf + 8 * i) = make_float2(acc[i][0], acc[i][1]);
  }
}
__device__ __forceinline__ void colsum_store(int b2, unsigned char* sm) {
  const float* sf = reinterpret_cast<const float*>(sm + 448 * 64);
  const int lane = threadIdx.x & 31;
  float s = 0.f;
#pragma unroll
  for (int i = 0; i < 7; i++) s += sf[i * 32 + lane];
  g_cs[(b2 >= 56 ? FF : 0) + (b2 % 56) * 32 + lane] = s;
}
__device__ __forceinline__ void wgmma_rs_n96(float (&d)[48], uint32_t a0, uint32_t a1, uint32_t a2, uint32_t a3, uint64_t db, int sc) {
  asm volatile("{\n.reg .pred p;\nsetp.ne.b32 p, %53, 0;\n"
    "wgmma.mma_async.sync.aligned.m64n96k16.f32.bf16.bf16 {%0, %1, %2, %3, %4, %5, %6, %7, %8, %9, %10, %11, %12, %13, %14, %15, %16, %17, %18, %19, %20, %21, %22, %23, %24, %25, %26, %27, %28, %29, %30, %31, %32, %33, %34, %35, %36, %37, %38, %39, %40, %41, %42, %43, %44, %45, %46, %47}, {%48, %49, %50, %51}, %52, p, 1, 1, 1;\n}\n"
    : "+f"(d[0]), "+f"(d[1]), "+f"(d[2]), "+f"(d[3]), "+f"(d[4]), "+f"(d[5]), "+f"(d[6]), "+f"(d[7]), "+f"(d[8]), "+f"(d[9]), "+f"(d[10]), "+f"(d[11]), "+f"(d[12]), "+f"(d[13]), "+f"(d[14]), "+f"(d[15]), "+f"(d[16]), "+f"(d[17]), "+f"(d[18]), "+f"(d[19]), "+f"(d[20]), "+f"(d[21]), "+f"(d[22]), "+f"(d[23]), "+f"(d[24]), "+f"(d[25]), "+f"(d[26]), "+f"(d[27]), "+f"(d[28]), "+f"(d[29]), "+f"(d[30]), "+f"(d[31]), "+f"(d[32]), "+f"(d[33]), "+f"(d[34]), "+f"(d[35]), "+f"(d[36]), "+f"(d[37]), "+f"(d[38]), "+f"(d[39]), "+f"(d[40]), "+f"(d[41]), "+f"(d[42]), "+f"(d[43]), "+f"(d[44]), "+f"(d[45]), "+f"(d[46]), "+f"(d[47])
    : "r"(a0), "r"(a1), "r"(a2), "r"(a3), "l"(db), "r"(sc));
}
__device__ __forceinline__ void wgmma_rs_n128(float (&d)[64], uint32_t a0, uint32_t a1, uint32_t a2, uint32_t a3, uint64_t db, int sc) {
  asm volatile("{\n.reg .pred p;\nsetp.ne.b32 p, %69, 0;\n"
    "wgmma.mma_async.sync.aligned.m64n128k16.f32.bf16.bf16 {%0, %1, %2, %3, %4, %5, %6, %7, %8, %9, %10, %11, %12, %13, %14, %15, %16, %17, %18, %19, %20, %21, %22, %23, %24, %25, %26, %27, %28, %29, %30, %31, %32, %33, %34, %35, %36, %37, %38, %39, %40, %41, %42, %43, %44, %45, %46, %47, %48, %49, %50, %51, %52, %53, %54, %55, %56, %57, %58, %59, %60, %61, %62, %63}, {%64, %65, %66, %67}, %68, p, 1, 1, 1;\n}\n"
    : "+f"(d[0]), "+f"(d[1]), "+f"(d[2]), "+f"(d[3]), "+f"(d[4]), "+f"(d[5]), "+f"(d[6]), "+f"(d[7]), "+f"(d[8]), "+f"(d[9]), "+f"(d[10]), "+f"(d[11]), "+f"(d[12]), "+f"(d[13]), "+f"(d[14]), "+f"(d[15]), "+f"(d[16]), "+f"(d[17]), "+f"(d[18]), "+f"(d[19]), "+f"(d[20]), "+f"(d[21]), "+f"(d[22]), "+f"(d[23]), "+f"(d[24]), "+f"(d[25]), "+f"(d[26]), "+f"(d[27]), "+f"(d[28]), "+f"(d[29]), "+f"(d[30]), "+f"(d[31]), "+f"(d[32]), "+f"(d[33]), "+f"(d[34]), "+f"(d[35]), "+f"(d[36]), "+f"(d[37]), "+f"(d[38]), "+f"(d[39]), "+f"(d[40]), "+f"(d[41]), "+f"(d[42]), "+f"(d[43]), "+f"(d[44]), "+f"(d[45]), "+f"(d[46]), "+f"(d[47]), "+f"(d[48]), "+f"(d[49]), "+f"(d[50]), "+f"(d[51]), "+f"(d[52]), "+f"(d[53]), "+f"(d[54]), "+f"(d[55]), "+f"(d[56]), "+f"(d[57]), "+f"(d[58]), "+f"(d[59]), "+f"(d[60]), "+f"(d[61]), "+f"(d[62]), "+f"(d[63])
    : "r"(a0), "r"(a1), "r"(a2), "r"(a3), "l"(db), "r"(sc));
}
__device__ __forceinline__ void wgmma_rs_n112(float (&d)[56], uint32_t a0, uint32_t a1, uint32_t a2, uint32_t a3, uint64_t db, int sc) {
  asm volatile("{\n.reg .pred p;\nsetp.ne.b32 p, %61, 0;\n"
    "wgmma.mma_async.sync.aligned.m64n112k16.f32.bf16.bf16 {%0, %1, %2, %3, %4, %5, %6, %7, %8, %9, %10, %11, %12, %13, %14, %15, %16, %17, %18, %19, %20, %21, %22, %23, %24, %25, %26, %27, %28, %29, %30, %31, %32, %33, %34, %35, %36, %37, %38, %39, %40, %41, %42, %43, %44, %45, %46, %47, %48, %49, %50, %51, %52, %53, %54, %55}, {%56, %57, %58, %59}, %60, p, 1, 1, 1;\n}\n"
    : "+f"(d[0]), "+f"(d[1]), "+f"(d[2]), "+f"(d[3]), "+f"(d[4]), "+f"(d[5]), "+f"(d[6]), "+f"(d[7]), "+f"(d[8]), "+f"(d[9]), "+f"(d[10]), "+f"(d[11]), "+f"(d[12]), "+f"(d[13]), "+f"(d[14]), "+f"(d[15]), "+f"(d[16]), "+f"(d[17]), "+f"(d[18]), "+f"(d[19]), "+f"(d[20]), "+f"(d[21]), "+f"(d[22]), "+f"(d[23]), "+f"(d[24]), "+f"(d[25]), "+f"(d[26]), "+f"(d[27]), "+f"(d[28]), "+f"(d[29]), "+f"(d[30]), "+f"(d[31]), "+f"(d[32]), "+f"(d[33]), "+f"(d[34]), "+f"(d[35]), "+f"(d[36]), "+f"(d[37]), "+f"(d[38]), "+f"(d[39]), "+f"(d[40]), "+f"(d[41]), "+f"(d[42]), "+f"(d[43]), "+f"(d[44]), "+f"(d[45]), "+f"(d[46]), "+f"(d[47]), "+f"(d[48]), "+f"(d[49]), "+f"(d[50]), "+f"(d[51]), "+f"(d[52]), "+f"(d[53]), "+f"(d[54]), "+f"(d[55])
    : "r"(a0), "r"(a1), "r"(a2), "r"(a3), "l"(db), "r"(sc));
}

struct cplx { float re, im; };
__device__ __forceinline__ cplx cmul(cplx a, cplx b) {
  cplx r; r.re = a.re * b.re - a.im * b.im; r.im = a.re * b.im + a.im * b.re; return r;
}
__device__ __forceinline__ cplx zpow_acc(float a2, float bt, float c) {
  float mag = ex2f(a2 * c);
  float tr = bt * c;
  tr -= rintf(tr);
  float ang = tr * 6.283185307179586f;
  cplx r; r.re = mag * __cosf(ang); r.im = mag * __sinf(ang); return r;
}

constexpr int SB_TAB  = 0;
constexpr int SB_WREG = 7168;
constexpr int UZ = 40;
constexpr int SB_U    = 4 * SB_WREG;
constexpr int SB_KV   = SB_U + 172 * 36;
constexpr int SB_TOTAL = (SB_KV + 644 * 4 + 127) / 128 * 128;
constexpr int SB_F3   = 0;
constexpr int SB_F2   = 1792;
constexpr int SB_Y    = 4096;
constexpr int SB_KD   = SB_Y;
constexpr int SB_KDO  = SB_KD + 2240;
constexpr int FR_LN = 4 * SB_TOTAL;
constexpr int FR_CS = (FR_LN + LN_SMEM + 127) / 128 * 128;
constexpr int FR_X = FR_CS + CS_SMEM;
constexpr int FRONT_SMEM = FR_X + 16384;
constexpr int FR_BAR = 229120 + 320;

__device__ __forceinline__ int rowaddr(int r) { return 32 * r + 16 * (r >> 2); }
struct hc { __half2 re, im; };
__device__ __forceinline__ hc bcast(cplx a) { hc r; r.re = __float2half2_rn(a.re); r.im = __float2half2_rn(a.im); return r; }
__device__ __forceinline__ hc hmul(hc v, hc s) {
  hc r;
  r.re = __hfma2(v.re, s.re, __hneg2(__hmul2(v.im, s.im)));
  r.im = __hfma2(v.re, s.im, __hmul2(v.im, s.re));
  return r;
}
__device__ __forceinline__ uint32_t h2u(__half2 h) { return *reinterpret_cast<uint32_t*>(&h); }
__device__ __forceinline__ void gen8(unsigned char* p, cplx s, cplx r1, hc r1sq, hc r2) {
  const cplx v1 = cmul(s, r1);
  hc p0; p0.re = __floats2half2_rn(s.re, v1.re); p0.im = __floats2half2_rn(s.im, v1.im);
  const hc p1 = hmul(p0, r1sq), p2 = hmul(p0, r2), p3 = hmul(p1, r2);
  *reinterpret_cast<uint4*>(p) = make_uint4(h2u(p0.re), h2u(p1.re), h2u(p2.re), h2u(p3.re));
  *reinterpret_cast<uint4*>(p + 8 * 112) = make_uint4(h2u(p0.im), h2u(p1.im), h2u(p2.im), h2u(p3.im));
}
__device__ __forceinline__ cplx csq(cplx a) { cplx r; r.re = a.re * a.re - a.im * a.im; r.im = 2.f * a.re * a.im; return r; }
__device__ __forceinline__ cplx cconj(cplx a) { a.im = -a.im; return a; }
__device__ __forceinline__ uint2 lds64(uint32_t a) { uint2 r; asm volatile("ld.shared.v2.u32 {%0,%1}, [%2];" : "=r"(r.x), "=r"(r.y) : "r"(a)); return r; }

__device__ __forceinline__ void mlp_bar_init(uint32_t base) {
  if ((threadIdx.x & 31) == 0 && (threadIdx.x >> 7) == 1) {
#pragma unroll 1
    for (int b = (threadIdx.x >> 5) - 4; b < 36; b += 4) mbar_init(base + 8 * b, ((b >= 10 && b < 13) || b == 28 || b >= 32) ? 2 : 1);
    asm volatile("fence.mbarrier_init.release.cluster;" ::: "memory");
  }
  __syncwarp();
}

__device__ __forceinline__ void front_phase(const bf16* __restrict__ Are, const bf16* __restrict__ Aim,
                                             const bf16* __restrict__ Bre, const bf16* __restrict__ Bim,
                                             const bf16* __restrict__ Cre, const bf16* __restrict__ Cim,
                                             const bf16* __restrict__ log_dt, const bf16* __restrict__ Dskip,
                                             const bf16* __restrict__ x, const bf16* __restrict__ wg,
                                             const bf16* __restrict__ wu, const bf16* __restrict__ wd,
                                             const CUtensorMap& tmU, const CUtensorMap& tmX) {
  extern __shared__ __align__(1024) unsigned char smem_all[];
  const int sub = threadIdx.x >> 7;
  const int tid = threadIdx.x & 127, lane = tid & 31;
  const int bar = 1 + sub;
  unsigned char* sm = smem_all + sub * SB_TOTAL;
  const uint32_t sbase = smem_u32(sm);
  const int w = ((tid >> 5) + sub) & 3;
  const int g = lane >> 2, t = lane & 3;
  const bool upper = threadIdx.x >= 256;
  const int hbar = upper ? 14 : 13;
  const bool do_ln = upper && blockIdx.x < 128;
  if (do_ln) ln1_load(x, blockIdx.x, smem_all + FR_LN);
  if (blockIdx.x >= 112) {
    mlp_bar_init(smem_u32(smem_all) + FR_BAR - 320);
    if (do_ln) ln1_tile(blockIdx.x, smem_all + FR_LN);
    if (upper) named_bar(hbar, 256);
    const int t0 = (blockIdx.x - 112) + (upper ? 20 : 0);
    unsigned char* cs = smem_all + (upper ? 3 * CS_SMEM : 0);
#pragma unroll
    for (int i = 0; i < 3; i++)
      if (t0 + 40 * i < 112) colsum_load(wg, wu, t0 + 40 * i, cs + i * CS_SMEM);
    for (int i = (blockIdx.x - 112) * 512 + threadIdx.x; i < FF * DM * 2 / 128; i += 20 * 512)
      asm volatile("prefetch.global.L2 [%0];" ::"l"(reinterpret_cast<const char*>(wd) + (size_t)i * 128));
    cp_async_wait_all();
    named_bar(hbar, 256);
#pragma unroll
    for (int i = 0; i < 3; i++)
      if (t0 + 40 * i < 112) colsum_reduce(cs + i * CS_SMEM);
    named_bar(hbar, 256);
    const int wi = (threadIdx.x >> 5) & 7;
    if (wi < 3 && t0 + 40 * wi < 112) colsum_store(t0 + 40 * wi, cs + wi * CS_SMEM);
    named_bar(hbar, 256);
    if ((threadIdx.x & 255) == 0) {
      asm volatile("fence.acq_rel.gpu;" ::: "memory");
      asm volatile("red.relaxed.gpu.global.add.u32 [%0], 1;" ::"l"(&g_cnt[8]) : "memory");
    }
    return;
  }
  const int d = blockIdx.x * 4 + sub;
  if ((threadIdx.x & 255) == 0) mbar_init(smem_u32(smem_all) + FR_BAR + (upper ? 8 : 0), 1);
  const int pidx = (d * NM + 64 * w) / 2 + lane;
  const uint32_t pAre = __ldg(reinterpret_cast<const uint32_t*>(Are) + pidx), pAim = __ldg(reinterpret_cast<const uint32_t*>(Aim) + pidx);
  const uint32_t pBre = __ldg(reinterpret_cast<const uint32_t*>(Bre) + pidx), pBim = __ldg(reinterpret_cast<const uint32_t*>(Bim) + pidx);
  const uint32_t pCre = __ldg(reinterpret_cast<const uint32_t*>(Cre) + pidx), pCim = __ldg(reinterpret_cast<const uint32_t*>(Cim) + pidx);
  const bf16 ldt_raw = log_dt[d];
  mlp_bar_init(smem_u32(smem_all) + FR_BAR - 320);
  const float dt = bf16r(expf(__bfloat162float(ldt_raw)));
  const uint32_t dsk2 = (uint32_t)__bfloat16_as_ushort(Dskip[d]) * 0x10001u;
  if (upper) ln1_tile(blockIdx.x, smem_all + FR_LN);
  if (tid < 90) *reinterpret_cast<uint4*>(sm + SB_U + tid * 16) = make_uint4(0, 0, 0, 0);
  if (tid >= 96 && tid < 105) *reinterpret_cast<uint4*>(sm + SB_U + 168 * 36 + (tid - 96) * 16) = make_uint4(0, 0, 0, 0);
  float w0re, w0im, w1re, w1im;
  {
    const float br0 = dt * bflo(pBre), bi0 = dt * bflo(pBim), br1 = dt * bfhi(pBre), bi1 = dt * bfhi(pBim);
    w0re = bflo(pCre) * br0 - bflo(pCim) * bi0; w0im = bflo(pCre) * bi0 + bflo(pCim) * br0;
    w1re = bfhi(pCre) * br1 - bfhi(pCim) * bi1; w1im = bfhi(pCre) * bi1 + bfhi(pCim) * br1;
  }
  float mx = fmaxf(fmaxf(fabsf(w0re), fabsf(w0im)), fmaxf(fabsf(w1re), fabsf(w1im)));
#pragma unroll
  for (int o = 16; o > 0; o >>= 1) mx = fmaxf(mx, __shfl_xor_sync(0xffffffffu, mx, o));
  int ex = (__float_as_uint(mx) >> 23) & 0xff;
  ex = min(max(ex, 1), 252);
  const float scale = __uint_as_float((uint32_t)(253 - ex) << 23);
  const float inv_scale = __uint_as_float((uint32_t)(ex + 1) << 23);

  float acc[5][4];
#pragma unroll
  for (int i = 0; i < 5; i++) { acc[i][0] = acc[i][1] = acc[i][2] = acc[i][3] = 0.f; }
  float k2048 = 0.f;
  unsigned char* tabw = sm + SB_TAB + w * SB_WREG;
  const uint32_t ldA = sbase + SB_TAB + w * SB_WREG + ((lane & 7) + 8 * ((lane >> 4) & 1)) * 112 + ((lane >> 3) & 1) * 16;
  const uint32_t ldB = sbase + SB_TAB + w * SB_WREG + ((lane & 7) + 8 * ((lane >> 3) & 1)) * 112 + 32 + (lane >> 4) * 16;
#pragma unroll 1
  for (int r = 0; r < 2; r++) {
    {
      const float a2 = dt * (r ? bfhi(pAre) : bflo(pAre)) * 1.4426950408889634f;
      const float bt = dt * (r ? bfhi(pAim) : bflo(pAim)) * 0.15915494309189535f;
      cplx W; W.re = (r ? w1re : w0re) * scale; W.im = -(r ? w1im : w0im) * scale;
      unsigned char* rec = tabw + ((lane >> 3) * 16 + (lane & 7)) * 112;
      const cplx y1 = zpow_acc(a2, -bt, 1.f), z8 = zpow_acc(a2, bt, 8.f), y128 = zpow_acc(a2, -bt, 128.f);
      const cplx y512 = zpow_acc(a2, -bt, 512.f), y1024 = zpow_acc(a2, -bt, 1024.f);
      const cplx z16 = csq(z8), z32 = csq(z16), z64 = csq(z32);
      const cplx y2 = csq(y1), y4 = csq(y2), y256 = csq(y128);
      cplx one; one.re = 1.f; one.im = 0.f;
      const hc h16 = bcast(z16), h32 = bcast(z32), h2 = bcast(y2), h4 = bcast(y4);
      const hc h128 = bcast(y128), h256 = bcast(y256), h512 = bcast(y512);
      gen8(rec, one, z8, h16, h32);
      gen8(rec + 16, z64, z8, h16, h32);
      gen8(rec + 32, W, y1, h2, h4);
      gen8(rec + 48, cmul(W, y128), y1, h2, h4);
      gen8(rec + 64, cmul(W, y256), y2, h4, h128);
      gen8(rec + 80, cmul(W, y512), y128, h256, h4);
      const cplx w1024 = cmul(W, y1024);
      gen8(rec + 96, w1024, y128, h256, h512);
      k2048 += w1024.re * y1024.re - w1024.im * y1024.im;
    }
    __syncwarp();
#pragma unroll
    for (int ks = 0; ks < 4; ks++) {
      uint32_t a0, a1, a2, a3, b0, b1, b2, b3;
      ldsm_x4_t(ldA + ks * 1792, a0, a1, a2, a3);
      ldsm_x4_t(ldB + ks * 1792, b0, b1, b2, b3);
      mma_f16(acc[0], a0, a1, a2, a3, b0, b1);
      mma_f16(acc[1], a0, a1, a2, a3, b2, b3);
      ldsm_x4_t(ldB + ks * 1792 + 32, b0, b1, b2, b3);
      mma_f16(acc[2], a0, a1, a2, a3, b0, b1);
      mma_f16(acc[3], a0, a1, a2, a3, b2, b3);
      ldsm_x2_t(ldB + ks * 1792 + 64, b0, b1);
      mma_f16(acc[4], a0, a1, a2, a3, b0, b1);
    }
    __syncwarp();
  }
  {
    float* red = reinterpret_cast<float*>(tabw);
#pragma unroll
    for (int hr = 0; hr < 2; hr++) {
      const int row = g + 8 * hr;
      *reinterpret_cast<float2*>(red + 8 * row + 2 * t) = make_float2(acc[0][2 * hr] * inv_scale, acc[0][2 * hr + 1] * inv_scale);
      *reinterpret_cast<float2*>(red + 128 + 8 * row + 2 * t) = make_float2(acc[1][2 * hr] * inv_scale, acc[1][2 * hr + 1] * inv_scale);
      *reinterpret_cast<float2*>(red + 256 + 64 * (t >> 1) + 2 * (t & 1) + 4 * row) = make_float2(acc[2][2 * hr] * inv_scale, acc[2][2 * hr + 1] * inv_scale);
      red[384 + 64 * (t & 1) + (t >> 1) + 2 * row] = acc[3][2 * hr] * inv_scale;
      red[384 + 64 * (t & 1) + 32 + (t >> 1) + 2 * row] = acc[3][2 * hr + 1] * inv_scale;
      red[512 + 32 * t + row] = acc[4][2 * hr] * inv_scale;
      red[512 + 32 * t + 16 + row] = acc[4][2 * hr + 1] * inv_scale;
    }
#pragma unroll
    for (int o = 16; o > 0; o >>= 1) k2048 += __shfl_xor_sync(0xffffffffu, k2048, o);
    if (lane == 0) red[640] = k2048 * inv_scale;
  }
  const uint32_t ubar = smem_u32(smem_all) + FR_BAR + (upper ? 8 : 0);
  const int ustg = upper ? FR_LN : FR_CS;
  if ((threadIdx.x & 255) == 0) {
    flag_wait(&g_cnt[7], (__ldcg(&g_epoch) + 1u) * 128u);
    asm volatile("fence.proxy.async.global;" ::: "memory");
    mbar_expect(ubar, 16384);
    tma2d(smem_u32(smem_all) + ustg, &tmU, ubar, (blockIdx.x * 4 + (sub & 2)) * 16, 0);
    tma2d(smem_u32(smem_all) + FR_X + (upper ? 8192 : 0), &tmX, ubar, (blockIdx.x * 4 + (sub & 2)) * 16, 0);
  }
  __syncwarp();
  named_bar(bar, 128);
  float* Kv = reinterpret_cast<float*>(sm + SB_KV);
  {
    const float* r0 = reinterpret_cast<const float*>(sm + SB_TAB);
    constexpr int WS = SB_WREG / 4;
    const float4 a = *reinterpret_cast<const float4*>(r0 + 4 * tid), b = *reinterpret_cast<const float4*>(r0 + WS + 4 * tid);
    const float4 c = *reinterpret_cast<const float4*>(r0 + 2 * WS + 4 * tid), e = *reinterpret_cast<const float4*>(r0 + 3 * WS + 4 * tid);
    *reinterpret_cast<float4*>(Kv + 4 * tid) =
        make_float4((a.x + b.x) + (c.x + e.x), (a.y + b.y) + (c.y + e.y), (a.z + b.z) + (c.z + e.z), (a.w + b.w) + (c.w + e.w));
    const int i = 512 + tid;
    Kv[i] = (r0[i] + r0[WS + i]) + (r0[2 * WS + i] + r0[3 * WS + i]);
    if (tid == 0) Kv[640] = (r0[640] + r0[WS + 640]) + (r0[2 * WS + 640] + r0[3 * WS + 640]);
  }
  named_bar(bar, 128);
  {
    auto tap_idx = [](int j) { const int m = j >> 1; const int r = (j & 1) ? m + (m & 1) : m; return min(max(j < 256 ? j : 128 + r, 0), 640); };
    float kd[3][3], f3[3], f2[3];
#pragma unroll
    for (int it = 0; it < 3; it++) {
      const int j = 528 - 2 * (tid + 128 * it);
#pragma unroll
      for (int e = 0; e < 3; e++) kd[it][e] = Kv[tap_idx(j + 1 - e)];
    }
    const int fa = tid >= 48, xa = tid - 48 * fa, ja = 144 - 2 * xa;
    const int fb = tid >> 6, xb = tid & 63, jb = 160 - 2 * xb;
#pragma unroll
    for (int e = 0; e < 3; e++) {
      f3[e] = Kv[min(max(384 + fa + 2 * (ja + 1 - e), 0), 640)];
      f2[e] = Kv[min(256 + fb + 2 * (jb + 1 - e), 640)];
    }
    const float k512 = Kv[384];
    uint32_t* ee = reinterpret_cast<uint32_t*>(sm + SB_KD);
#pragma unroll
    for (int it = 0; it < 3; it++) {
      const int x = tid + 128 * it, j = 528 - 2 * x;
      const float k0 = (j >= -1 && j <= 508) ? kd[it][0] : 0.f;
      float k1 = (j >= 0 && j <= 510) ? kd[it][1] : 0.f;
      const float k2 = (j >= 1 && j <= 510) ? kd[it][2] : 0.f;
      if (j == 510) k1 -= k512;
      const uint32_t we = pack_bf16(k1, k2), wo = pack_bf16(k0, k1);
      if (x < 272) { ee[2 * x] = we; ee[560 + 2 * x] = wo; }
      if (x < 272 && x >= 4) { ee[2 * x - 7] = we; ee[560 + 2 * x - 7] = wo; }
    }
    {
      const int hi = 128 - fa;
      const float k0 = (ja + 1 >= 64 && ja + 1 <= hi) ? f3[0] : 0.f, k1 = (ja >= 64 && ja <= hi) ? f3[1] : 0.f;
      const float k2 = (ja - 1 >= 64 && ja - 1 <= hi) ? f3[2] : 0.f;
      const uint32_t we = pack_bf16(k1, k2), wo = pack_bf16(k0, k1);
      uint32_t* p = reinterpret_cast<uint32_t*>(sm + SB_F3) + fa * 224;
      if (tid < 96) { p[2 * xa] = we; p[112 + 2 * xa] = wo; }
      if (tid < 96 && xa < 44) { p[2 * xa + 9] = we; p[112 + 2 * xa + 9] = wo; }
    }
    {
      const float k0 = (jb + 1 >= 64 && jb + 1 <= 127) ? f2[0] : 0.f, k1 = (jb >= 64 && jb <= 127) ? f2[1] : 0.f;
      const float k2 = (jb - 1 >= 64 && jb - 1 <= 127) ? f2[2] : 0.f;
      const uint32_t we = pack_bf16(k1, k2), wo = pack_bf16(k0, k1);
      uint32_t* p = reinterpret_cast<uint32_t*>(sm + SB_F2) + fb * 288;
      p[2 * xb] = we; p[144 + 2 * xb] = wo;
      p[2 * xb + 17] = we; p[144 + 2 * xb + 17] = wo;
    }
  }
  const float k1024 = Kv[512];
  named_bar(hbar, 256);
  mbar_wait(ubar, 0);
#pragma unroll
  for (int k = 0; k < 2; k++) {
    const int c = tid + 128 * k;
    *reinterpret_cast<uint4*>(sm + SB_U + rowaddr((c >> 1) + UZ) + (c & 1) * 16) =
        *reinterpret_cast<const uint4*>(smem_all + ustg + (c >> 1) * 64 + (sub & 1) * 32 + (c & 1) * 16);
  }
  named_bar(hbar, 256);
  const int krow = (lane & 7) + 8 * ((lane >> 3) & 1);
  if (w < 2) {
    float acd[4][2][4];
#pragma unroll
    for (int c = 0; c < 4; c++)
#pragma unroll
      for (int i = 0; i < 2; i++)
#pragma unroll
        for (int e = 0; e < 4; e++) acd[c][i][e] = 0.f;
    const uint32_t aQ = sbase + SB_U + rowaddr(UZ + 64 * w + 4 * krow) + (lane >> 4) * 16;
    const uint32_t pb = sbase + ((g & 1) ? SB_KDO + ((529 - g) / 2 + t) * 8 : SB_KD + ((528 - g) / 2 + t) * 8);
    uint32_t Q[36][4];
#define QOFF(j) (32 * (j) + 16 * (((j) + 64) / 4 - 16))
#pragma unroll
    for (int n = 0; n < 5; n++) ldsm_x4(aQ + QOFF(3 - n), Q[n][0], Q[n][1], Q[n][2], Q[n][3]);
#pragma unroll
    for (int q = 0; q < 33; q++) {
      if (q + 5 < 36) ldsm_x4(aQ + QOFF(3 - (q + 5)), Q[q + 5][0], Q[q + 5][1], Q[q + 5][2], Q[q + 5][3]);
      const uint2 e0 = lds64(pb - 32 * (2 * q));
      const uint2 e1 = lds64(pb - 32 * (2 * q + 1));
#pragma unroll
      for (int c = 0; c < 4; c++) {
        mma_bf16(acd[c][0], Q[3 - c + q][0], Q[3 - c + q][1], Q[3 - c + q][2], Q[3 - c + q][3], e0.x, e0.y);
        mma_bf16(acd[c][1], Q[3 - c + q][0], Q[3 - c + q][1], Q[3 - c + q][2], Q[3 - c + q][3], e1.x, e1.y);
      }
    }
#undef QOFF
    const int yl = (64 * (16 * w + g) + 2 * t + 16 * (g & 1) + 8 * ((g >> 1) & 1)) * 4;
    unsigned char* yb = sm + SB_Y + 8192;
#pragma unroll
    for (int c = 0; c < 4; c++)
#pragma unroll
      for (int nu = 0; nu < 2; nu++)
#pragma unroll
        for (int hr = 0; hr < 2; hr++)
          *reinterpret_cast<float2*>(yb + ((yl ^ ((16 * c + 8 * (nu ^ (c >> 1))) * 4)) + hr * 2048)) = make_float2(acd[c][nu][2 * hr], acd[c][nu][2 * hr + 1]);
  } else {
    const int yl = (16 * (g ^ ((g >> 2) & 1)) + 2 * t + 8 * ((g >> 1) & 1)) * 4;
    if (w == 2) {
      float ac[7][2][4];
#pragma unroll
      for (int T = 0; T < 7; T++)
#pragma unroll
        for (int i = 0; i < 2; i++)
#pragma unroll
          for (int e = 0; e < 4; e++) ac[T][i][e] = 0.f;
      uint32_t BA[2][4];
#pragma unroll
      for (int ks = 0; ks < 2; ks++)
#pragma unroll
        for (int r = 0; r < 4; r++) {
          uint32_t v = 0;
#pragma unroll
          for (int e = 0; e < 2; e++) {
            const int dlt = (2 * t + e + 8 * (r >> 1) + 16 * ks - 8) - g;
            const bool on = (r & 1) ? (dlt >= -5 && dlt <= -3) : (dlt >= -2 && dlt <= 2);
            v |= on ? (0x3f80u << (16 * e)) : 0u;
          }
          BA[ks][r] = v;
        }
      const int chl = 2 * UZ + (lane & 7) + (lane >> 3) - 1;
      const uint32_t ub = sbase + SB_U + rowaddr(chl >> 1) + (chl & 1) * 16;
      const uint32_t fb = sbase + SB_F2 + (80 - (g - t)) * 8;
#pragma unroll
      for (int sp = 0; sp < 2; sp++) {
        uint32_t bb[2][7][2];
#pragma unroll
        for (int i = 0; i < 7 - sp; i++) {
          const int beta = 11 - sp - 2 * i;
#pragma unroll
          for (int o = 0; o < 2; o++) {
            uint32_t u0, u1, u2, u3;
            ldsm_x4(ub + (2 * beta + o) * 144, u0, u1, u2, u3);
            float z[4] = {0.f, 0.f, 0.f, 0.f};
            mma_bf16(z, BA[0][0], BA[0][1], BA[0][2], BA[0][3], u0, u1);
            mma_bf16(z, BA[1][0], BA[1][1], BA[1][2], BA[1][3], u2, u3);
            bb[0][i][o] = pack_bf16(z[0], z[1]);
            bb[1][i][o] = pack_bf16(z[2], z[3]);
          }
        }
#pragma unroll
        for (int f = 0; f < 2; f++) {
#pragma unroll
          for (int k = 0; k < 3; k++) {
#pragma unroll
            for (int nu = 0; nu < 2; nu++) {
              const uint2 A01 = lds64(fb + f * 1152 + nu * 576 - 32 * (6 + 2 * (2 * k + sp)));
              const uint2 A23 = lds64(fb + f * 1152 + nu * 576 - 32 * (5 + 2 * (2 * k + sp)));
#pragma unroll
              for (int i = 0; i < 7 - sp; i++) {
                const int T = 7 - i + k;
                if (T <= 7) mma_bf16(ac[T - 1][nu], A01.x, A01.y, A23.x, A23.y, bb[f][i][0], bb[f][i][1]);
              }
            }
          }
        }
      }
      named_bar(5 + bar, 96);
      unsigned char* yb = sm + SB_Y;
#pragma unroll
      for (int T = 0; T <= 7; T++)
#pragma unroll
        for (int nu = 0; nu < 2; nu++)
#pragma unroll
          for (int hr = 0; hr < 2; hr++)
            *reinterpret_cast<float2*>(yb + ((yl ^ ((8 * (nu ^ hr)) * 4)) + (16 * T + 8 * hr) * 64)) =
                T ? make_float2(ac[T ? T - 1 : 0][nu][2 * hr], ac[T ? T - 1 : 0][nu][2 * hr + 1]) : make_float2(0.f, 0.f);
    } else {
      float ac[5][2][4];
#pragma unroll
      for (int T = 0; T < 5; T++)
#pragma unroll
        for (int i = 0; i < 2; i++)
#pragma unroll
          for (int e = 0; e < 4; e++) ac[T][i][e] = 0.f;
      const uint32_t fb = sbase + SB_F3 + ((g & 1) ? 448 + ((145 - g) / 2 + t) * 8 : ((144 - g) / 2 + t) * 8);
      uint32_t ur[3];
#pragma unroll
      for (int sg = 0; sg < 3; sg++) ur[sg] = sbase + SB_U + rowaddr(UZ + (lane & 7) + 8 * (lane >> 4) + sg - 1) + ((lane >> 3) & 1) * 16;
#pragma unroll 1
      for (int f = 0; f < 2; f++) {
        uint32_t BA[3][4];
        const int lo = f ? -11 : -4, hi = f ? -5 : 4;
#pragma unroll
        for (int sg = 0; sg < 3; sg++)
#pragma unroll
          for (int r = 0; r < 4; r++) {
            uint32_t v = 0;
#pragma unroll
            for (int e = 0; e < 2; e++) {
              const int dlt = (2 * t + e + 8 * (r >> 1) + 16 * (sg - 1)) - (g + 8 * (r & 1));
              v |= (dlt >= lo && dlt <= hi) ? (0x3f80u << (16 * e)) : 0u;
            }
            BA[sg][r] = v;
          }
        uint2 A01[5], A23[5];
#pragma unroll
        for (int s = 0; s < 5; s++) {
          A01[s] = lds64(fb + f * 896 - 32 * (8 + 2 * s));
          A23[s] = lds64(fb + f * 896 - 32 * (7 + 2 * s));
        }
#pragma unroll
        for (int beta = 3; beta >= -1; beta--) {
          float z0[4] = {0.f, 0.f, 0.f, 0.f}, z1[4] = {0.f, 0.f, 0.f, 0.f};
#pragma unroll
          for (int sg = 0; sg < 3; sg++) {
            uint32_t u0, u1, u2, u3;
            ldsm_x4(ur[sg] + beta * 576, u0, u1, u2, u3);
            mma_bf16(z0, BA[sg][0], BA[sg][1], BA[sg][2], BA[sg][3], u0, u1);
            mma_bf16(z1, BA[sg][0], BA[sg][1], BA[sg][2], BA[sg][3], u2, u3);
          }
          const uint32_t b0 = pack_bf16(z0[0], z0[1]), b1 = pack_bf16(z1[0], z1[1]);
          const uint32_t b2 = pack_bf16(z0[2], z0[3]), b3 = pack_bf16(z1[2], z1[3]);
#pragma unroll
          for (int s = 0; s < 5; s++) {
            const int T = beta + 4 + s;
            if (T <= 7) {
              mma_bf16(ac[T - 3][0], A01[s].x, A01[s].y, A23[s].x, A23[s].y, b0, b1);
              mma_bf16(ac[T - 3][1], A01[s].x, A01[s].y, A23[s].x, A23[s].y, b2, b3);
            }
          }
        }
      }
      {
        const uint32_t nk = (uint32_t)__bfloat16_as_ushort(__float2bfloat16_rn(-k1024));
        uint32_t PC[5];
#pragma unroll
        for (int m = 0; m < 5; m++) {
          const int j = 8 * (125 + m) + g - 2 * t;
          PC[m] = ((j == 1020 || j == 1021) ? nk : 0u) | ((j == 1021 || j == 1022) ? (nk << 16) : 0u);
        }
#pragma unroll
        for (int k = 0; k < 2; k++) {
          const uint32_t ab = sbase + SB_U + rowaddr(UZ + 48 - 63 - k + krow) + (lane >> 4) * 16;
#pragma unroll
          for (int T = 3; T <= 7; T++) {
            uint32_t a0, a1, a2, a3;
            ldsm_x4(ab + (T - 3) * 576, a0, a1, a2, a3);
            mma_bf16(ac[T - 3][0], a0, a1, a2, a3, PC[1 + 2 * k], PC[2 * k]);
            mma_bf16(ac[T - 3][1], a0, a1, a2, a3, PC[2 + 2 * k], PC[1 + 2 * k]);
          }
        }
      }
      unsigned char* yb = sm + SB_Y + 16384;
#pragma unroll
      for (int T = 0; T <= 7; T++)
#pragma unroll
        for (int nu = 0; nu < 2; nu++)
#pragma unroll
          for (int hr = 0; hr < 2; hr++)
            *reinterpret_cast<float2*>(yb + ((yl ^ ((8 * (nu ^ hr)) * 4)) + (16 * T + 8 * hr) * 64)) =
                T >= 3 ? make_float2(ac[T >= 3 ? T - 3 : 0][nu][2 * hr], ac[T >= 3 ? T - 3 : 0][nu][2 * hr + 1]) : make_float2(0.f, 0.f);
    }
  }
  if (w < 2) asm volatile("bar.arrive %0, 96;" ::"r"(5 + bar) : "memory");
  named_bar(bar, 128);
  {
    const __nv_bfloat162 ds = *reinterpret_cast<const __nv_bfloat162*>(&dsk2);
    const int r0 = tid >> 2, ch = tid & 3;
    const int yo = (16 * (r0 ^ ((r0 >> 2) & 1)) + ((4 * ch) ^ (8 * (((r0 >> 1) ^ (r0 >> 3)) & 1)))) * 4;
    const int uo = SB_U + rowaddr(r0 + UZ) + ch * 8;
#pragma unroll
    for (int k = 0; k < 4; k++) {
      const float4 a = *reinterpret_cast<const float4*>(sm + SB_Y + yo + k * 2048);
      const float4 b = *reinterpret_cast<const float4*>(sm + SB_Y + 8192 + yo + k * 2048);
      const float4 c = *reinterpret_cast<const float4*>(sm + SB_Y + 16384 + yo + k * 2048);
      const uint2 uw = *reinterpret_cast<const uint2*>(sm + uo + k * 1152);
      const uint2 xw = *reinterpret_cast<const uint2*>(smem_all + FR_X + (sub >> 1) * 8192 + r0 * 64 + (sub & 1) * 32 + ch * 8 + k * 2048);
      const uint32_t y0 = pack_bf16(b.x + (a.x + c.x), b.y + (a.y + c.y)), y1 = pack_bf16(b.z + (a.z + c.z), b.w + (a.w + c.w));
      const __nv_bfloat162 h0 = __hadd2_rn(*reinterpret_cast<const __nv_bfloat162*>(&xw.x),
          __hadd2_rn(*reinterpret_cast<const __nv_bfloat162*>(&y0), __hmul2_rn(*reinterpret_cast<const __nv_bfloat162*>(&uw.x), ds)));
      const __nv_bfloat162 h1 = __hadd2_rn(*reinterpret_cast<const __nv_bfloat162*>(&xw.y),
          __hadd2_rn(*reinterpret_cast<const __nv_bfloat162*>(&y1), __hmul2_rn(*reinterpret_cast<const __nv_bfloat162*>(&uw.y), ds)));
      *reinterpret_cast<uint2*>(g_hT + (size_t)d * SEQ + tid * 4 + k * 512) =
          make_uint2(*reinterpret_cast<const uint32_t*>(&h0), *reinterpret_cast<const uint32_t*>(&h1));
    }
  }
  if (threadIdx.x < 480) {
    asm volatile("bar.arrive 11, 512;" ::: "memory");
  } else {
    fence_async();
    asm volatile("bar.arrive 15, 512;" ::: "memory");
    named_bar(11, 512);
    if (lane == 0) {
      asm volatile("fence.acq_rel.gpu;" ::: "memory");
      asm volatile("red.relaxed.gpu.global.add.u32 [%0], 1;" ::"l"(&g_cnt[blockIdx.x >> 4]) : "memory");
    }
    __syncwarp();
  }
}

constexpr int M_A     = 0;
constexpr int M_W     = 7 * 16384;
constexpr int M_XB    = M_W + 3 * 32768;
constexpr int M_CS    = M_XB + 14336;
constexpr int M_BAR   = M_CS + 1792;
constexpr int M_TOTAL = M_BAR + 384;

template <int NCB, int NA>
__device__ __forceinline__ void g1_pack(const float (&acc)[NA], uint32_t* pk, const float* cs, float mb0, float mb1, int lane) {
  const int t = lane & 3;
#pragma unroll
  for (int cb = 0; cb < NCB; cb++) {
    const float2 sc = *reinterpret_cast<const float2*>(cs + cb * 8 + 2 * t);
    pk[2 * cb]     = pack_bf16(fmaf(-mb0, sc.x, acc[4 * cb + 0]), fmaf(-mb0, sc.y, acc[4 * cb + 1]));
    pk[2 * cb + 1] = pack_bf16(fmaf(-mb1, sc.x, acc[4 * cb + 2]), fmaf(-mb1, sc.y, acc[4 * cb + 3]));
  }
}
__device__ __forceinline__ uint32_t glu2(uint32_t gw, uint32_t uw, float hr) {
  float t0, t1;
  asm("tanh.approx.f32 %0, %1;" : "=f"(t0) : "f"(bflo(gw) * hr));
  asm("tanh.approx.f32 %0, %1;" : "=f"(t1) : "f"(bfhi(gw) * hr));
  return pack_bf16(fmaf(t0, hr, hr) * bflo(uw), fmaf(t1, hr, hr) * bfhi(uw));
}
__device__ __forceinline__ uint32_t w2_slot(int j, int kp) {
  const int sl = j % 10;
  if (sl < 6) return M_W + ((sl >> 1) + 2) % 3 * 32768 + (sl & 1) * 16384;
  const int i = sl - 6;
  return M_A + (i + (i >= kp ? 3 : 0)) * 16384;
}

__global__ void __cluster_dims__(2, 1, 1) __launch_bounds__(512, 1)
k_all(const bf16* __restrict__ Are, const bf16* __restrict__ Aim, const bf16* __restrict__ Bre, const bf16* __restrict__ Bim,
      const bf16* __restrict__ Cre, const bf16* __restrict__ Cim, const bf16* __restrict__ log_dt, const bf16* __restrict__ Dskip,
      const bf16* __restrict__ x, const bf16* __restrict__ wgp, const bf16* __restrict__ wup, const bf16* __restrict__ wdp,
      const __grid_constant__ CUtensorMap tmLu, const __grid_constant__ CUtensorMap tmLx,
      const __grid_constant__ CUtensorMap tmA, const __grid_constant__ CUtensorMap tmG,
      const __grid_constant__ CUtensorMap tmU, const __grid_constant__ CUtensorMap tmD, bf16* __restrict__ out) {
  extern __shared__ __align__(1024) unsigned char smem[];
  const uint32_t sb = smem_u32(smem);
  const int tid = threadIdx.x, lane = tid & 31, warp = tid >> 5;
  const uint32_t barA = sb + M_BAR, barF = barA + 56, barE = barF + 24, barS = barE + 24;
  const uint32_t barW2 = barS + 8, barAf = barW2 + 112, barX = barAf + 8, barH = barX + 8, barE2 = barH + 16;
  if (sb & 1023) __trap();
  if (tid >= 224 && tid < 230) prefetch_tm(tid == 224 ? &tmG : tid == 225 ? &tmU : tid == 226 ? &tmA : tid == 227 ? &tmD : tid == 228 ? &tmLu : &tmLx);
  __syncwarp();

  front_phase(Are, Aim, Bre, Bim, Cre, Cim, log_dt, Dskip, x, wgp, wup, wdp, tmLu, tmLx);

  fence_async();
  if (warp < 15 || blockIdx.x >= 112) named_bar(15, 512);
  const uint32_t rank = blockIdx.x & 1;
  const bool live = blockIdx.x < 128;
  const int pr = live ? blockIdx.x >> 1 : 0;
  const int mt = pr & 15;
  const int fp = pr >> 4;
  const int fj = 4 * rank + fp;
  const int kp = min((112 * fp) >> 6, 4);
  cluster_arrive();

  if (warp >= 8) {
    const unsigned int ep = __ldcg(&g_epoch);
    asm volatile("setmaxnreg.dec.sync.aligned.u32 24;");
    if (!live || warp >= 12) {
      cluster_wait();
      if (warp == 9) { named_bar(2, 288); named_bar(3, 288); }
    } else if (warp == 8) {
      if (lane == 0) {
        for (int it = 0; it < 14; it++) {
          const int s = it % 3, rnd = it / 3;
          const bool pb = it >= 7;
          const int kb = pb ? it - 7 : it;
          if (rnd > 0) mbar_wait(barE + 8 * s, (rnd - 1) & 1);
          mbar_expect(barF + 8 * s, 32768);
          const uint32_t dst = sb + M_W + s * 32768;
          const int c0 = 224 * fj + (pb ? 128 : 0);
          tma2d(dst, &tmG, barF + 8 * s, c0, 64 * kb);
          tma2d(dst + 16384, &tmU, barF + 8 * s, c0, 64 * kb);
          tma2d(dst + 8192, &tmG, barF + 8 * s, c0 + 64, 64 * kb);
          tma2d(dst + 24576, &tmU, barF + 8 * s, c0 + 64, 64 * kb);
        }
        for (int j = 0; j < 14; j++) {
          if (j < 6 && !(j & 1)) { const int it = 11 + (j >> 1); mbar_wait(barE + 8 * (it % 3), (it / 3) & 1); }
          if (j == 6) mbar_wait(barAf, 0);
          if (j >= 10) mbar_wait(barE2 + 8 * (j - 10), 0);
          mbar_expect(barW2 + 8 * j, 16384);
          const uint32_t dst = sb + w2_slot(j, kp);
#pragma unroll
          for (int h = 0; h < 2; h++) {
            const int u = 2 * j + h;
            int c, o;
            if (u < 7) { c = 0; o = u; } else if (u < 19) { c = 1 + (u - 7) / 4; o = (u - 7) % 4; } else { c = 1 + (u - 19) / 3; o = 4 + (u - 19) % 3; }
            const int row = (4 * rank + ((fp + c) & 3)) * 224 + 32 * o;
            tma2d(dst + h * 4096, &tmD, barW2 + 8 * j, 112 * fp, row);
            tma2d(dst + 8192 + h * 4096, &tmD, barW2 + 8 * j, 112 * fp + 64, row);
          }
        }
      }
      __syncwarp();
      cluster_wait();
    } else if (warp == 9) {
      if (lane < 7) flag_wait(&g_cnt[lane], (ep + 1u) * 16u);
      cluster_wait();
      if (lane == 0) {
        asm volatile("fence.proxy.async.global;" ::: "memory");
        for (int k = 0; k < 7; k++) {
          mbar_expect(barA + 8 * k, 16384);
          tma3d_mc(sb + M_A + k * 16384 + rank * 8192, &tmA, barA + 8 * k, 0, 64 * k, 2 * mt + rank, (uint16_t)3);
        }
      }
      __syncwarp();
#pragma unroll 1
      for (int p = 0; p < 2; p++) {
        named_bar(2 + p, 288);
        if (lane == 0) {
          asm volatile("fence.acq_rel.gpu;" ::: "memory");
          asm volatile("red.relaxed.gpu.global.add.u32 [%0], 1;" ::"l"(&g_cnt2[(mt * 2 + rank) * 2 + p]) : "memory");
        }
        __syncwarp();
      }
    } else if (warp == 10) {
      cluster_wait();
      if (lane == 0) {
#pragma unroll 1
        for (int p = 0; p < 2; p++) {
          flag_wait(&g_cnt2[(mt * 2 + rank) * 2 + p], (ep + 1u) * 4u);
          mbar_arrive(barH + 8 * p);
        }
      }
    } else {
      if (lane == 0) flag_wait(&g_cnt[8], (ep + 1u) * 40u);
      __syncwarp();
      float* cs = reinterpret_cast<float*>(smem + M_CS);
      for (int i = lane; i < 448; i += 32) cs[i] = __ldcg(&g_cs[(i >= 224 ? FF + i - 224 : i) + fj * 224]);
      __syncwarp();
      if (lane == 0) mbar_arrive(barS);
      cluster_wait();
    }
    __syncwarp();
    cluster_arrive(); cluster_wait();
  } else {
    asm volatile("setmaxnreg.inc.sync.aligned.u32 232;");
    const int wg = warp >> 2, wq = warp & 3;
    const bool elect = (tid & 127) == 0;
    const float* cs = reinterpret_cast<const float*>(smem + M_CS);
#define RELEASE(b) do { if (elect) mbar_arrive(b); } while (0)
#define PUBLISH(p) asm volatile("bar.arrive %0, 288;" ::"r"(2 + (p)) : "memory")
    const int dr = (lane & 7) + 8 * (lane >> 4), tc = 2 * wq + ((lane >> 3) & 1);
    const uint32_t aT = sb + M_A + wg * 8192 + dr * 128 + ((tc ^ (lane & 7)) << 4);
    uint4* hbase = (live ? reinterpret_cast<uint4*>(g_P) : reinterpret_cast<uint4*>(const_cast<bf16*>(wdp))) + (size_t)(mt * 8 * 8 + warp) * (14 * 32) + lane;
    const uint32_t dead = live ? 0u : 1u;
    float mb0, rs0, mb1, rs1;
    uint32_t pkA[64];
    {
      float accA[64], accB[64];
      float s0 = 0.f, q0 = 0.f, s1 = 0.f, q1 = 0.f;
#pragma unroll
      for (int kb = 0; kb < 7; kb++) {
        const int s = kb % 3;
        mbar_wait(barA + 8 * kb, (0) | dead);
        uint32_t af[4][4];
#pragma unroll
        for (int k = 0; k < 4; k++) ldsm_x4_t(aT + kb * 16384 + k * 2048, af[k][0], af[k][1], af[k][2], af[k][3]);
        mbar_wait(barF + 8 * s, ((kb / 3) & 1) | dead);
        const uint64_t db = mk_desc(sb + M_W + s * 32768, 8192, 1024, 1);
        wg_fence();
#pragma unroll
        for (int k = 0; k < 4; k++) {
          wgmma_rs_n128(accA, af[k][0], af[k][1], af[k][2], af[k][3], db + k * 128, (kb | k) != 0);
          wgmma_rs_n128(accB, af[k][0], af[k][1], af[k][2], af[k][3], db + 1024 + k * 128, (kb | k) != 0);
        }
        wg_commit();
        if (kb > 0) { wg_wait<1>(); RELEASE(barE + 8 * ((kb - 1) % 3)); }
#pragma unroll
        for (int k = 0; k < 4; k++) {
#pragma unroll
          for (int h = 0; h < 2; h++) {
            const float a = bflo(af[k][2 * h]), b = bfhi(af[k][2 * h]), c = bflo(af[k][2 * h + 1]), e = bfhi(af[k][2 * h + 1]);
            s0 += a + b; q0 = fmaf(a, a, fmaf(b, b, q0));
            s1 += c + e; q1 = fmaf(c, c, fmaf(e, e, q1));
          }
        }
      }
#pragma unroll
      for (int o = 1; o <= 2; o <<= 1) {
        s0 += __shfl_xor_sync(0xffffffffu, s0, o); q0 += __shfl_xor_sync(0xffffffffu, q0, o);
        s1 += __shfl_xor_sync(0xffffffffu, s1, o); q1 += __shfl_xor_sync(0xffffffffu, q1, o);
      }
      s0 *= (1.0f / DM); s1 *= (1.0f / DM);
      mb0 = bf16r(s0); mb1 = bf16r(s1);
      rs0 = 0.5f * ln_rden(fmaxf(q0 * (1.0f / DM) - s0 * s0, 0.f));
      rs1 = 0.5f * ln_rden(fmaxf(q1 * (1.0f / DM) - s1 * s1, 0.f));
      mbar_wait(barS, (0) | dead);
      wg_wait<0>();
      RELEASE(barE + 0);
      g1_pack<16, 64>(accA, pkA, cs, mb0, mb1, lane);
      g1_pack<16, 64>(accB, pkA + 32, cs + 224, mb0, mb1, lane);
    }
    uint32_t hf[56];
    uint4* hown = live ? hbase + (size_t)fj * (8 * 14 * 32) : reinterpret_cast<uint4*>(g_dummy) + lane;
    {
      float accG[48], accU[48];
#pragma unroll
      for (int kb = 0; kb < 7; kb++) {
        const int it = kb + 7, s = it % 3;
        uint32_t af[4][4];
#pragma unroll
        for (int k = 0; k < 4; k++) ldsm_x4_t(aT + kb * 16384 + k * 2048, af[k][0], af[k][1], af[k][2], af[k][3]);
        mbar_wait(barF + 8 * s, ((it / 3) & 1) | dead);
        const uint64_t db = mk_desc(sb + M_W + s * 32768, 8192, 1024, 1);
        wg_fence();
#pragma unroll
        for (int k = 0; k < 4; k++) {
          wgmma_rs_n96(accG, af[k][0], af[k][1], af[k][2], af[k][3], db + k * 128, (kb | k) != 0);
          wgmma_rs_n96(accU, af[k][0], af[k][1], af[k][2], af[k][3], db + 1024 + k * 128, (kb | k) != 0);
        }
        wg_commit();
        if (kb > 0) { wg_wait<1>(); RELEASE(barE + 8 * ((it - 1) % 3)); }
        if (kb < 4) {
#pragma unroll
          for (int i = 0; i < 8; i++) hf[8 * kb + i] = glu2(pkA[8 * kb + i], pkA[32 + 8 * kb + i], (i & 1) ? rs1 : rs0);
          hown[(2 * kb) * 32] = make_uint4(hf[8 * kb], hf[8 * kb + 1], hf[8 * kb + 2], hf[8 * kb + 3]);
          hown[(2 * kb + 1) * 32] = make_uint4(hf[8 * kb + 4], hf[8 * kb + 5], hf[8 * kb + 6], hf[8 * kb + 7]);
          if (kb == 3) PUBLISH(0);
        }
      }
      wg_wait<0>();
      if (elect) { mbar_arrive(barE + 8 * (13 % 3)); mbar_arrive(barAf); }
#pragma unroll
      for (int cb = 0; cb < 12; cb++) {
        const float2 sg = *reinterpret_cast<const float2*>(cs + 128 + cb * 8 + 2 * (lane & 3));
        const float2 su = *reinterpret_cast<const float2*>(cs + 352 + cb * 8 + 2 * (lane & 3));
#pragma unroll
        for (int h = 0; h < 2; h++) {
          const float mb = h ? mb1 : mb0, hr = h ? rs1 : rs0;
          float t0, t1;
          asm("tanh.approx.f32 %0, %1;" : "=f"(t0) : "f"(fmaf(-mb, sg.x, accG[4 * cb + 2 * h]) * hr));
          asm("tanh.approx.f32 %0, %1;" : "=f"(t1) : "f"(fmaf(-mb, sg.y, accG[4 * cb + 2 * h + 1]) * hr));
          hf[32 + 2 * cb + h] = pack_bf16(fmaf(t0, hr, hr) * fmaf(-mb, su.x, accU[4 * cb + 2 * h]), fmaf(t1, hr, hr) * fmaf(-mb, su.y, accU[4 * cb + 2 * h + 1]));
        }
      }
    }
#pragma unroll
    for (int q = 0; q < 6; q++) hown[(8 + q) * 32] = make_uint4(hf[32 + 4 * q], hf[33 + 4 * q], hf[34 + 4 * q], hf[35 + 4 * q]);
    PUBLISH(1);
    float acc[56];
    auto hsrc = [&](int i) -> const uint4* {
      int c, o;
      if (i < 38) { c = 1 + (i - 14) / 8; o = (i - 14) % 8; } else { c = 1 + (i - 38) / 6; o = 8 + (i - 38) % 6; }
      return hbase + (size_t)(4 * rank + ((fp + c) & 3)) * (8 * 14 * 32) + o * 32;
    };
    uint4 hq[6][4];
#pragma unroll
    for (int j = 0; j < 14; j++) {
      if (j == 0) mbar_wait(barH, dead);
      if (j == 7) mbar_wait(barH + 8, dead);
#pragma unroll
      for (int k = 0; k < 4; k++) {
        if (j == 0 && k >= 2) hq[3][k] = __ldcg(hsrc(12 + k));
        if (j <= 4) hq[(j + 4) % 6][k] = __ldcg(hsrc(4 * (j + 4) + k));
        if (j >= 7 && j <= 11) hq[(j + 2) % 6][k] = __ldcg(hsrc(4 * (j + 2) + k));
      }
      mbar_wait(barW2 + 8 * j, (0) | dead);
      const uint64_t db = mk_desc(sb + w2_slot(j, kp), 8192, 1024, 1);
      wg_fence();
#pragma unroll
      for (int k = 0; k < 4; k++) {
        const int i = 4 * j + k;
        if (i < 14) wgmma_rs_n112(acc, hf[4 * i], hf[4 * i + 1], hf[4 * i + 2], hf[4 * i + 3], db + k * 128, i != 0);
        else wgmma_rs_n112(acc, hq[j % 6][k].x, hq[j % 6][k].y, hq[j % 6][k].z, hq[j % 6][k].w, db + k * 128, 1);
      }
      wg_commit();
      if (j > 0) { wg_wait<1>(); if (j <= 4) RELEASE(barE2 + 8 * (j - 1)); }
    }
    wg_wait<0>();
    cluster_wait();
    if (wg != (int)rank) {
      asm volatile("bar.arrive 1, 256;" ::: "memory");
      const uint32_t xd = mapa(sb + M_XB, rank ^ 1) + (tid & 127) * 16;
      const uint32_t xb = mapa(barX, rank ^ 1);
#pragma unroll
      for (int q = 0; q < 7; q++)
        asm volatile("st.async.weak.shared::cluster.mbarrier::complete_tx::bytes.v4.b32 [%0], {%1,%2,%3,%4}, [%5];"
                     ::"r"(xd + q * 2048), "r"(pack_bf16(acc[8 * q], acc[8 * q + 1])), "r"(pack_bf16(acc[8 * q + 2], acc[8 * q + 3])),
                       "r"(pack_bf16(acc[8 * q + 4], acc[8 * q + 5])), "r"(pack_bf16(acc[8 * q + 6], acc[8 * q + 7])), "r"(xb) : "memory");
    } else {
      uint32_t hr[7][4];
      const int d0 = 112 * fp;
#pragma unroll
      for (int q = 0; q < 7; q++) {
        const int dd = d0 + 16 * q;
        ldsm_x4_t(aT + (dd >> 6) * 16384 + (dd & 63) * 128, hr[q][0], hr[q][1], hr[q][2], hr[q][3]);
      }
      if (elect) mbar_expect(barX, 14336);
      mbar_wait(barX, 0);
      const uint32_t stg = sb + M_W + wq * 3840;
      const uint32_t so = stg + ((lane & 7) + 8 * ((lane >> 3) & 1)) * 240 + (lane >> 4) * 16;
      named_bar(1, 256);
#pragma unroll
      for (int q = 0; q < 7; q++) {
        const uint4 v = *reinterpret_cast<const uint4*>(smem + M_XB + q * 2048 + (tid & 127) * 16);
        const uint32_t m0 = pack_bf16(acc[8 * q] + bflo(v.x), acc[8 * q + 1] + bfhi(v.x)), m1 = pack_bf16(acc[8 * q + 2] + bflo(v.y), acc[8 * q + 3] + bfhi(v.y));
        const uint32_t m2 = pack_bf16(acc[8 * q + 4] + bflo(v.z), acc[8 * q + 5] + bfhi(v.z)), m3 = pack_bf16(acc[8 * q + 6] + bflo(v.w), acc[8 * q + 7] + bfhi(v.w));
        stsm_x4(so + q * 32, hadd2_bf16(hr[q][0], m0), hadd2_bf16(hr[q][1], m1), hadd2_bf16(hr[q][2], m2), hadd2_bf16(hr[q][3], m3));
      }
      __syncwarp();
      bf16* o = live ? out + (size_t)(mt * 128 + 64 * wg + 16 * wq) * DM + d0 : g_dummy;
#pragma unroll
      for (int k = 0; k < 7; k++) {
        const int c = lane + 32 * k;
        const int r = c / 14, ch = c - 14 * r;
        *reinterpret_cast<uint4*>(o + (size_t)r * DM + ch * 8) = *reinterpret_cast<const uint4*>(smem + M_W + wq * 3840 + r * 240 + ch * 16);
      }
    }
    if (tid == 0 && live) {
      const unsigned int n = atomicAdd(&g_done, 1u);
      if ((n & 127u) == 127u) atomicAdd(&g_epoch, 1u);
    }
    __syncwarp();
    cluster_arrive(); cluster_wait();
#undef PUBLISH
#undef RELEASE
  }
}

typedef CUresult (*EncFn)(CUtensorMap*, CUtensorMapDataType, cuuint32_t, void*, const cuuint64_t*, const cuuint64_t*,
                          const cuuint32_t*, const cuuint32_t*, CUtensorMapInterleave, CUtensorMapSwizzle,
                          CUtensorMapL2promotion, CUtensorMapFloatOOBfill);

static void make_map(EncFn enc, CUtensorMap* tm, const void* ptr, int rank, const uint64_t* dims, const uint64_t* strides_bytes,
                     const uint32_t* box, CUtensorMapSwizzle swz) {
  cuuint64_t gd[3], gs[2]; cuuint32_t bd[3], es[3] = {1, 1, 1};
  for (int i = 0; i < rank; i++) { gd[i] = dims[i]; bd[i] = box[i]; }
  for (int i = 0; i < rank - 1; i++) gs[i] = strides_bytes[i];
  enc(tm, CU_TENSOR_MAP_DATA_TYPE_BFLOAT16, rank, const_cast<void*>(ptr), gd, gs, bd, es, CU_TENSOR_MAP_INTERLEAVE_NONE, swz,
      CU_TENSOR_MAP_L2_PROMOTION_L2_128B, CU_TENSOR_MAP_FLOAT_OOB_FILL_NONE);
}

template <class K, class... Args>
static void launch_k(K kern, int grid, int block, int smem, bool pdl, Args... args) {
  cudaLaunchConfig_t cfg = {};
  cfg.gridDim = dim3(grid); cfg.blockDim = dim3(block); cfg.dynamicSmemBytes = smem; cfg.stream = cudaStreamPerThread;
  cudaLaunchAttribute at[1];
  at[0].id = cudaLaunchAttributeProgrammaticStreamSerialization;
  at[0].val.programmaticStreamSerializationAllowed = 1;
  cfg.attrs = at; cfg.numAttrs = pdl ? 1 : 0;
  cudaLaunchKernelEx(&cfg, kern, args...);
}

extern "C" void kernel_launch(void* const* d_in, const int* in_sizes, int n_in, void* d_out, int out_size) {
  const bf16* x   = (const bf16*)d_in[0];
  const bf16* Are = (const bf16*)d_in[1];
  const bf16* Aim = (const bf16*)d_in[2];
  const bf16* Bre = (const bf16*)d_in[3];
  const bf16* Bim = (const bf16*)d_in[4];
  const bf16* Cre = (const bf16*)d_in[5];
  const bf16* Cim = (const bf16*)d_in[6];
  const bf16* ldt = (const bf16*)d_in[7];
  const bf16* dsk = (const bf16*)d_in[8];
  const bf16* wg  = (const bf16*)d_in[10];
  const bf16* wu  = (const bf16*)d_in[11];
  const bf16* wd  = (const bf16*)d_in[12];

  static EncFn enc = nullptr;
  static void *p_hT = nullptr, *p_uT = nullptr, *p_xT = nullptr;
  if (!enc) {
    void* fn = nullptr; cudaDriverEntryPointQueryResult qr;
    cudaGetDriverEntryPoint("cuTensorMapEncodeTiled", &fn, cudaEnableDefault, &qr);
    enc = (EncFn)fn;
    cudaGetSymbolAddress(&p_hT, g_hT);
    cudaGetSymbolAddress(&p_uT, g_uT);
    cudaGetSymbolAddress(&p_xT, g_xT);
    cudaFuncSetAttribute(k_all, cudaFuncAttributeMaxDynamicSharedMemorySize, M_TOTAL);
  }
  CUtensorMap tmA, tmG, tmU, tmD, tmLu, tmLx;
  {
    uint64_t dims[2] = {DM * 16, SEQ / 16}, st[1] = {DM * 32};
    uint32_t box[2] = {32, 128};
    make_map(enc, &tmLu, p_uT, 2, dims, st, box, CU_TENSOR_MAP_SWIZZLE_NONE);
    make_map(enc, &tmLx, p_xT, 2, dims, st, box, CU_TENSOR_MAP_SWIZZLE_NONE);
  }
  {
    uint64_t dims[3] = {64, DM, SEQ / 64}, st[2] = {SEQ * 2, 128};
    uint32_t box[3] = {64, 64, 1};
    make_map(enc, &tmA, p_hT, 3, dims, st, box, CU_TENSOR_MAP_SWIZZLE_128B);
  }
  {
    uint64_t dims[2] = {FF, DM}, st[1] = {FF * 2};
    uint32_t box[2] = {64, 64};
    make_map(enc, &tmG, wg, 2, dims, st, box, CU_TENSOR_MAP_SWIZZLE_128B);
    make_map(enc, &tmU, wu, 2, dims, st, box, CU_TENSOR_MAP_SWIZZLE_128B);
  }
  {
    uint64_t dims[2] = {DM, FF}, st[1] = {DM * 2};
    uint32_t box[2] = {64, 32};
    make_map(enc, &tmD, wd, 2, dims, st, box, CU_TENSOR_MAP_SWIZZLE_128B);
  }
  static_assert(FR_BAR == M_BAR + 320 && FR_BAR + 16 <= M_TOTAL, "barrier placement");
  static_assert(FRONT_SMEM <= M_XB, "front phase must not touch the MLP barriers");
  launch_k(k_all, 132, 512, M_TOTAL, false, Are, Aim, Bre, Bim, Cre, Cim, ldt, dsk, x, wg, wu, wd, tmLu, tmLx, tmA, tmG, tmU, tmD, (bf16*)d_out);
}
```

```cpp
#include <cuda_runtime.h>
#include <cuda_bf16.h>
#include <cuda_fp16.h>
#include <cuda.h>
#include <stdint.h>

typedef __nv_bfloat16 bf16;

constexpr int SEQ = 2048;
constexpr int DM  = 448;
constexpr int NM  = 256;
constexpr int FF  = 1792;

struct __align__(1024) Scratch {
  bf16  uT[DM * SEQ];
  bf16  xT[DM * SEQ];
  bf16  hT[DM * SEQ];
  bf16  P[SEQ * FF];
  bf16  dummy[16 * DM];
  float cs[2 * FF];
  unsigned int cnt[32];
  unsigned int cnt2[64];
  unsigned int epoch;
  unsigned int done;
};
__device__ Scratch g_scr;

__device__ __forceinline__ uint32_t smem_u32(const void* p) { return (uint32_t)__cvta_generic_to_shared(p); }
__device__ __forceinline__ float bf16r(float v) { return __bfloat162float(__float2bfloat16_rn(v)); }
__device__ __forceinline__ float bflo(uint32_t w) { return __uint_as_float(w << 16); }
__device__ __forceinline__ float bfhi(uint32_t w) { return __uint_as_float(w & 0xffff0000u); }
__device__ __forceinline__ uint32_t pack_bf16(float lo, float hi) {
  uint32_t r; asm("cvt.rn.bf16x2.f32 %0, %1, %2;" : "=r"(r) : "f"(hi), "f"(lo)); return r;
}
__device__ __forceinline__ uint32_t pack_f16(float lo, float hi) {
  uint32_t r; asm("cvt.rn.f16x2.f32 %0, %1, %2;" : "=r"(r) : "f"(hi), "f"(lo)); return r;
}
__device__ __forceinline__ float ex2f(float x) { float r; asm("ex2.approx.ftz.f32 %0, %1;" : "=f"(r) : "f"(x)); return r; }
__device__ __forceinline__ float ln_rden(float var) {
  float sq, r;
  asm("sqrt.approx.ftz.f32 %0, %1;" : "=f"(sq) : "f"(bf16r(bf16r(var) + 1e-5f)));
  asm("rcp.approx.ftz.f32 %0, %1;" : "=f"(r) : "f"(bf16r(sq)));
  return r;
}
__device__ __forceinline__ uint32_t hadd2_bf16(uint32_t a, uint32_t b) {
  const __nv_bfloat162 r = __hadd2_rn(*reinterpret_cast<const __nv_bfloat162*>(&a), *reinterpret_cast<const __nv_bfloat162*>(&b));
  return *reinterpret_cast<const uint32_t*>(&r);
}
__device__ __forceinline__ void pdl_launch() { asm volatile("griddepcontrol.launch_dependents;"); }
__device__ __forceinline__ void pdl_wait() { asm volatile("griddepcontrol.wait;" ::: "memory"); }

__device__ __forceinline__ void mbar_init(uint32_t a, int c) { asm volatile("mbarrier.init.shared::cta.b64 [%0], %1;" ::"r"(a), "r"(c)); }
__device__ __forceinline__ void mbar_expect(uint32_t a, uint32_t bytes) {
  asm volatile("mbarrier.arrive.expect_tx.shared::cta.b64 _, [%0], %1;" ::"r"(a), "r"(bytes) : "memory");
}
__device__ __forceinline__ void mbar_arrive(uint32_t a) { asm volatile("mbarrier.arrive.shared::cta.b64 _, [%0];" ::"r"(a) : "memory"); }
__device__ __forceinline__ void mbar_arrive_cluster(uint32_t remote_a) {
  asm volatile("mbarrier.arrive.shared::cluster.b64 _, [%0];" ::"r"(remote_a) : "memory");
}
__device__ __forceinline__ void mbar_wait(uint32_t a, uint32_t ph) {
  uint32_t ok; int it = 0;
  do {
    asm volatile("{.reg .pred p; mbarrier.try_wait.parity.shared::cta.b64 p, [%1], %2; selp.u32 %0,1,0,p;}"
                 : "=r"(ok) : "r"(a), "r"(ph) : "memory");
  } while (!ok && ++it < (1 << 24));
}
__device__ __forceinline__ void flag_wait(const unsigned int* p, unsigned int target) {
  unsigned int v; int it = 0;
  asm volatile("ld.acquire.gpu.global.u32 %0, [%1];" : "=r"(v) : "l"(p) : "memory");
  if ((int)(v - target) >= 0) return;
  while (true) {
    __nanosleep(32);
    asm volatile("ld.relaxed.gpu.global.u32 %0, [%1];" : "=r"(v) : "l"(p) : "memory");
    if ((int)(v - target) >= 0 || ++it > (1 << 22)) break;
  }
  asm volatile("ld.acquire.gpu.global.u32 %0, [%1];" : "=r"(v) : "l"(p) : "memory");
}
__device__ __forceinline__ uint4 ld_relaxed_v4(const uint4* p) {
  uint4 v; asm volatile("ld.relaxed.gpu.global.v4.u32 {%0,%1,%2,%3}, [%4];" : "=r"(v.x), "=r"(v.y), "=r"(v.z), "=r"(v.w) : "l"(p) : "memory"); return v;
}
__device__ __forceinline__ void st_relaxed_v4(uint4* p, uint32_t a, uint32_t b, uint32_t c, uint32_t d) {
  asm volatile("st.relaxed.gpu.global.v4.u32 [%0], {%1,%2,%3,%4};" ::"l"(p), "r"(a), "r"(b), "r"(c), "r"(d) : "memory");
}
__device__ __forceinline__ uint32_t mapa(uint32_t a, uint32_t rank) {
  uint32_t r; asm volatile("mapa.shared::cluster.u32 %0, %1, %2;" : "=r"(r) : "r"(a), "r"(rank)); return r;
}
__device__ __forceinline__ void cluster_arrive() { asm volatile("barrier.cluster.arrive.relaxed.aligned;" ::: "memory"); }
__device__ __forceinline__ void cluster_wait() { asm volatile("barrier.cluster.wait.acquire.aligned;" ::: "memory"); }
__device__ __forceinline__ void fence_async() { asm volatile("fence.proxy.async.shared::cta;" ::: "memory"); }
__device__ __forceinline__ void named_bar(int id, int n) { asm volatile("bar.sync %0, %1;" ::"r"(id), "r"(n) : "memory"); }

__device__ __forceinline__ void tma2d(uint32_t dst, const CUtensorMap* tm, uint32_t bar, int c0, int c1) {
  asm volatile("cp.async.bulk.tensor.2d.shared::cluster.global.mbarrier::complete_tx::bytes [%0], [%1, {%3,%4}], [%2];"
               ::"r"(dst), "l"(tm), "r"(bar), "r"(c0), "r"(c1) : "memory");
}
__device__ __forceinline__ void tma3d(uint32_t dst, const CUtensorMap* tm, uint32_t bar, int c0, int c1, int c2) {
  asm volatile("cp.async.bulk.tensor.3d.shared::cluster.global.mbarrier::complete_tx::bytes [%0], [%1, {%3,%4,%5}], [%2];"
               ::"r"(dst), "l"(tm), "r"(bar), "r"(c0), "r"(c1), "r"(c2) : "memory");
}
__device__ __forceinline__ void tma3d_mc(uint32_t dst, const CUtensorMap* tm, uint32_t bar, int c0, int c1, int c2, uint16_t mask) {
  asm volatile("cp.async.bulk.tensor.3d.shared::cluster.global.mbarrier::complete_tx::bytes.multicast::cluster [%0], [%1, {%3,%4,%5}], [%2], %6;"
               ::"r"(dst), "l"(tm), "r"(bar), "r"(c0), "r"(c1), "r"(c2), "h"(mask) : "memory");
}
__device__ __forceinline__ void tma2d_store(const CUtensorMap* tm, uint32_t src, int c0, int c1) {
  asm volatile("cp.async.bulk.tensor.2d.global.shared::cta.bulk_group [%0, {%2,%3}], [%1];"
               ::"l"(tm), "r"(src), "r"(c0), "r"(c1) : "memory");
}
__device__ __forceinline__ void bulk_commit() { asm volatile("cp.async.bulk.commit_group;" ::: "memory"); }
template <int N> __device__ __forceinline__ void bulk_wait_read() { asm volatile("cp.async.bulk.wait_group.read %0;" ::"n"(N) : "memory"); }
template <int N> __device__ __forceinline__ void bulk_wait() { asm volatile("cp.async.bulk.wait_group %0;" ::"n"(N) : "memory"); }
__device__ __forceinline__ void prefetch_tm(const CUtensorMap* tm) { asm volatile("prefetch.tensormap [%0];" ::"l"(tm) : "memory"); }

__device__ __forceinline__ void wg_fence() { asm volatile("wgmma.fence.sync.aligned;" ::: "memory"); }
__device__ __forceinline__ void wg_commit() { asm volatile("wgmma.commit_group.sync.aligned;" ::: "memory"); }
template <int N> __device__ __forceinline__ void wg_wait() { asm volatile("wgmma.wait_group.sync.aligned %0;" ::"n"(N) : "memory"); }
__device__ __forceinline__ uint64_t mk_desc(uint32_t addr, uint32_t lbo, uint32_t sbo, uint32_t swz) {
  return (uint64_t)((addr & 0x3FFFF) >> 4) | ((uint64_t)(lbo >> 4) << 16) | ((uint64_t)(sbo >> 4) << 32) | ((uint64_t)swz << 62);
}
__device__ __forceinline__ void ldsm_x4(uint32_t a, uint32_t& r0, uint32_t& r1, uint32_t& r2, uint32_t& r3) {
  asm volatile("ldmatrix.sync.aligned.m8n8.x4.shared.b16 {%0,%1,%2,%3}, [%4];" : "=r"(r0), "=r"(r1), "=r"(r2), "=r"(r3) : "r"(a));
}
__device__ __forceinline__ void ldsm_x4_t(uint32_t a, uint32_t& r0, uint32_t& r1, uint32_t& r2, uint32_t& r3) {
  asm volatile("ldmatrix.sync.aligned.m8n8.x4.trans.shared.b16 {%0,%1,%2,%3}, [%4];" : "=r"(r0), "=r"(r1), "=r"(r2), "=r"(r3) : "r"(a));
}
__device__ __forceinline__ void ldsm_x2_t(uint32_t a, uint32_t& r0, uint32_t& r1) {
  asm volatile("ldmatrix.sync.aligned.m8n8.x2.trans.shared.b16 {%0,%1}, [%2];" : "=r"(r0), "=r"(r1) : "r"(a));
}
__device__ __forceinline__ void stsm_x4(uint32_t a, uint32_t r0, uint32_t r1, uint32_t r2, uint32_t r3) {
  asm volatile("stmatrix.sync.aligned.m8n8.x4.shared.b16 [%0], {%1,%2,%3,%4};" ::"r"(a), "r"(r0), "r"(r1), "r"(r2), "r"(r3) : "memory");
}
__device__ __forceinline__ void stsm_x2(uint32_t a, uint32_t r0, uint32_t r1) {
  asm volatile("stmatrix.sync.aligned.m8n8.x2.shared.b16 [%0], {%1,%2};" ::"r"(a), "r"(r0), "r"(r1) : "memory");
}
__device__ __forceinline__ uint32_t lds32(uint32_t a) { uint32_t r; asm volatile("ld.shared.u32 %0, [%1];" : "=r"(r) : "r"(a)); return r; }
__device__ __forceinline__ void mma_bf16(float (&c)[4], uint32_t a0, uint32_t a1, uint32_t a2, uint32_t a3, uint32_t b0, uint32_t b1) {
  asm volatile("mma.sync.aligned.m16n8k16.row.col.f32.bf16.bf16.f32 {%0,%1,%2,%3}, {%4,%5,%6,%7}, {%8,%9}, {%0,%1,%2,%3};"
               : "+f"(c[0]), "+f"(c[1]), "+f"(c[2]), "+f"(c[3]) : "r"(a0), "r"(a1), "r"(a2), "r"(a3), "r"(b0), "r"(b1));
}
__device__ __forceinline__ void mma_f16(float (&c)[4], uint32_t a0, uint32_t a1, uint32_t a2, uint32_t a3, uint32_t b0, uint32_t b1) {
  asm volatile("mma.sync.aligned.m16n8k16.row.col.f32.f16.f16.f32 {%0,%1,%2,%3}, {%4,%5,%6,%7}, {%8,%9}, {%0,%1,%2,%3};"
               : "+f"(c[0]), "+f"(c[1]), "+f"(c[2]), "+f"(c[3]) : "r"(a0), "r"(a1), "r"(a2), "r"(a3), "r"(b0), "r"(b1));
}
__device__ __forceinline__ void cp_async16(uint32_t dst, const void* src) {
  asm volatile("cp.async.cg.shared.global [%0], [%1], 16;" ::"r"(dst), "l"(src) : "memory");
}
__device__ __forceinline__ void cp_async_wait_all() { asm volatile("cp.async.wait_all;" ::: "memory"); }

constexpr int LN_PITCH = 912;
constexpr int LN_STAT  = 16 * LN_PITCH;
constexpr int LN_SMEM  = LN_STAT + 7 * 128;
__device__ __forceinline__ void ln1_load(const bf16* __restrict__ x, int tile, unsigned char* sm) {
  const int r = (threadIdx.x >> 4) & 15, c = threadIdx.x & 15;
  const uint32_t dst = smem_u32(sm) + r * LN_PITCH + c * 16;
  const bf16* src = x + (size_t)(tile * 16 + r) * DM + c * 8;
#pragma unroll
  for (int k = 0; k < 4; k++)
    if (k < 3 || c < 8) cp_async16(dst + k * 256, src + k * 128);
}
__device__ __forceinline__ void ln1_tile(Scratch* __restrict__ S, int tile, unsigned char* sm) {
  const uint32_t sb = smem_u32(sm);
  const int lane = threadIdx.x & 31, w = (threadIdx.x >> 5) - 8;
  const int g = lane >> 2, t = lane & 3;
  cp_async_wait_all();
  named_bar(14, 256);
  if (w < 7) {
    float s1[4] = {0.f, 0.f, 0.f, 0.f}, qa[4] = {0.f, 0.f, 0.f, 0.f}, qb[4] = {0.f, 0.f, 0.f, 0.f};
    const uint32_t ad = sb + ((lane & 7) + 8 * ((lane >> 3) & 1)) * LN_PITCH + (lane >> 4) * 16 + w * 128;
#pragma unroll
    for (int k = 0; k < 4; k++) {
      uint32_t a0, a1, a2, a3;
      ldsm_x4(ad + k * 32, a0, a1, a2, a3);
      mma_bf16(s1, a0, a1, a2, a3, 0x3f803f80u, 0x3f803f80u);
      mma_bf16(qa, a0, a1, a2, a3, a0, a2);
      mma_bf16(qb, a0, a1, a2, a3, a1, a3);
    }
    if (t == (g >> 1)) {
      float2* st = reinterpret_cast<float2*>(sm + LN_STAT) + w * 16;
      st[g]     = make_float2(s1[0], (g & 1) ? qa[1] : qa[0]);
      st[g + 8] = make_float2(s1[2], (g & 1) ? qb[3] : qb[2]);
    }
  }
  named_bar(14, 256);
  if (w < 7) {
    float mb[4], rd[4];
    {
      const float2* st = reinterpret_cast<const float2*>(sm + LN_STAT) + (lane & 15);
      float sx = 0.f, sy = 0.f;
#pragma unroll
      for (int i = 0; i < 7; i++) { const float2 p = st[16 * i]; sx += p.x; sy += p.y; }
      const float mean = sx * (1.0f / DM);
      const float var = fmaxf(sy * (1.0f / DM) - mean * mean, 0.f);
      const float m = bf16r(mean);
      const float r = ln_rden(var);
#pragma unroll
      for (int e = 0; e < 4; e++) {
        mb[e] = __shfl_sync(0xffffffffu, m, 4 * t + e);
        rd[e] = __shfl_sync(0xffffffffu, r, 4 * t + e);
      }
    }
    const int r8 = lane & 7;
    const int tok = 4 * (r8 >> 1) + (r8 & 1) + 2 * ((lane >> 3) & 1);
    const uint32_t ad = sb + tok * LN_PITCH + (w * 64 + (lane >> 4) * 8) * 2;
    const size_t go = (size_t)(tile * DM + w * 64 + g) * 16 + 4 * t;
#pragma unroll
    for (int k = 0; k < 4; k++) {
      uint32_t v[4];
      ldsm_x4_t(ad + k * 32, v[0], v[1], v[2], v[3]);
#pragma unroll
      for (int h = 0; h < 2; h++) {
        const uint32_t d0 = pack_bf16(bflo(v[2 * h]) - mb[0], bfhi(v[2 * h]) - mb[1]);
        const uint32_t d1 = pack_bf16(bflo(v[2 * h + 1]) - mb[2], bfhi(v[2 * h + 1]) - mb[3]);
        const size_t o = go + (size_t)(16 * k + 8 * h) * 16;
        *reinterpret_cast<uint2*>(S->uT + o) = make_uint2(pack_bf16(bflo(d0) * rd[0], bfhi(d0) * rd[1]), pack_bf16(bflo(d1) * rd[2], bfhi(d1) * rd[3]));
        *reinterpret_cast<uint2*>(S->xT + o) = make_uint2(v[2 * h], v[2 * h + 1]);
      }
    }
    asm volatile("bar.arrive 12, 256;" ::: "memory");
  } else {
    named_bar(12, 256);
    if (lane == 0) {
      asm volatile("fence.acq_rel.gpu;" ::: "memory");
      asm volatile("red.relaxed.gpu.global.add.u32 [%0], 1;" ::"l"(&S->cnt[7]) : "memory");
    }
    __syncwarp();
  }
}

constexpr int CS_SMEM = 448 * 64 + 16 * 128;
__device__ __forceinline__ void colsum_load(const bf16* __restrict__ wg, const bf16* __restrict__ wu, int b2, unsigned char* sm) {
  const bf16* W = (b2 >= 56 ? wu : wg) + (b2 % 56) * 32;
  const uint32_t sb = smem_u32(sm);
#pragma unroll
  for (int k = 0; k < 7; k++)
    cp_async16(sb + (threadIdx.x & 255) * 16 + k * 4096, W + (size_t)((threadIdx.x & 255) >> 2) * FF + (threadIdx.x & 3) * 8 + (size_t)k * 64 * FF);
}
__device__ __forceinline__ void colsum_reduce(unsigned char* sm) {
  const int lane = threadIdx.x & 31, w = (threadIdx.x >> 5) & 7;
  if (w >= 7) return;
  float acc[4][4];
#pragma unroll
  for (int i = 0; i < 4; i++) { acc[i][0] = acc[i][1] = acc[i][2] = acc[i][3] = 0.f; }
  const uint32_t ad = smem_u32(sm) + (w * 64 + (lane & 15)) * 64 + (lane >> 4) * 16;
#pragma unroll
  for (int k = 0; k < 4; k++) {
#pragma unroll
    for (int h = 0; h < 2; h++) {
      uint32_t b0, b1, b2, b3;
      ldsm_x4_t(ad + k * 1024 + h * 32, b0, b1, b2, b3);
      mma_bf16(acc[2 * h], 0x3f803f80u, 0x3f803f80u, 0x3f803f80u, 0x3f803f80u, b0, b1);
      mma_bf16(acc[2 * h + 1], 0x3f803f80u, 0x3f803f80u, 0x3f803f80u, 0x3f803f80u, b2, b3);
    }
  }
  if (lane < 4) {
    float* sf = reinterpret_cast<float*>(sm + 448 * 64) + w * 32 + 2 * lane;
#pragma unroll
    for (int i = 0; i < 4; i++) *reinterpret_cast<float2*>(sf + 8 * i) = make_float2(acc[i][0], acc[i][1]);
  }
}
__device__ __forceinline__ void colsum_store(Scratch* __restrict__ S, int b2, unsigned char* sm) {
  const float* sf = reinterpret_cast<const float*>(sm + 448 * 64);
  const int lane = threadIdx.x & 31;
  float s = 0.f;
#pragma unroll
  for (int i = 0; i < 7; i++) s += sf[i * 32 + lane];
  S->cs[(b2 >= 56 ? FF : 0) + (b2 % 56) * 32 + lane] = s;
}
__device__ __forceinline__ void wgmma_rs_n96(float (&d)[48], uint32_t a0, uint32_t a1, uint32_t a2, uint32_t a3, uint64_t db, int sc) {
  asm volatile("{\n.reg .pred p;\nsetp.ne.b32 p, %53, 0;\n"
    "wgmma.mma_async.sync.aligned.m64n96k16.f32.bf16.bf16 {%0, %1, %2, %3, %4, %5, %6, %7, %8, %9, %10, %11, %12, %13, %14, %15, %16, %17, %18, %19, %20, %21, %22, %23, %24, %25, %26, %27, %28, %29, %30, %31, %32, %33, %34, %35, %36, %37, %38, %39, %40, %41, %42, %43, %44, %45, %46, %47}, {%48, %49, %50, %51}, %52, p, 1, 1, 1;\n}\n"
    : "+f"(d[0]), "+f"(d[1]), "+f"(d[2]), "+f"(d[3]), "+f"(d[4]), "+f"(d[5]), "+f"(d[6]), "+f"(d[7]), "+f"(d[8]), "+f"(d[9]), "+f"(d[10]), "+f"(d[11]), "+f"(d[12]), "+f"(d[13]), "+f"(d[14]), "+f"(d[15]), "+f"(d[16]), "+f"(d[17]), "+f"(d[18]), "+f"(d[19]), "+f"(d[20]), "+f"(d[21]), "+f"(d[22]), "+f"(d[23]), "+f"(d[24]), "+f"(d[25]), "+f"(d[26]), "+f"(d[27]), "+f"(d[28]), "+f"(d[29]), "+f"(d[30]), "+f"(d[31]), "+f"(d[32]), "+f"(d[33]), "+f"(d[34]), "+f"(d[35]), "+f"(d[36]), "+f"(d[37]), "+f"(d[38]), "+f"(d[39]), "+f"(d[40]), "+f"(d[41]), "+f"(d[42]), "+f"(d[43]), "+f"(d[44]), "+f"(d[45]), "+f"(d[46]), "+f"(d[47])
    : "r"(a0), "r"(a1), "r"(a2), "r"(a3), "l"(db), "r"(sc));
}
__device__ __forceinline__ void wgmma_rs_n128(float (&d)[64], uint32_t a0, uint32_t a1, uint32_t a2, uint32_t a3, uint64_t db, int sc) {
  asm volatile("{\n.reg .pred p;\nsetp.ne.b32 p, %69, 0;\n"
    "wgmma.mma_async.sync.aligned.m64n128k16.f32.bf16.bf16 {%0, %1, %2, %3, %4, %5, %6, %7, %8, %9, %10, %11, %12, %13, %14, %15, %16, %17, %18, %19, %20, %21, %22, %23, %24, %25, %26, %27, %28, %29, %30, %31, %32, %33, %34, %35, %36, %37, %38, %39, %40, %41, %42, %43, %44, %45, %46, %47, %48, %49, %50, %51, %52, %53, %54, %55, %56, %57, %58, %59, %60, %61, %62, %63}, {%64, %65, %66, %67}, %68, p, 1, 1, 1;\n}\n"
    : "+f"(d[0]), "+f"(d[1]), "+f"(d[2]), "+f"(d[3]), "+f"(d[4]), "+f"(d[5]), "+f"(d[6]), "+f"(d[7]), "+f"(d[8]), "+f"(d[9]), "+f"(d[10]), "+f"(d[11]), "+f"(d[12]), "+f"(d[13]), "+f"(d[14]), "+f"(d[15]), "+f"(d[16]), "+f"(d[17]), "+f"(d[18]), "+f"(d[19]), "+f"(d[20]), "+f"(d[21]), "+f"(d[22]), "+f"(d[23]), "+f"(d[24]), "+f"(d[25]), "+f"(d[26]), "+f"(d[27]), "+f"(d[28]), "+f"(d[29]), "+f"(d[30]), "+f"(d[31]), "+f"(d[32]), "+f"(d[33]), "+f"(d[34]), "+f"(d[35]), "+f"(d[36]), "+f"(d[37]), "+f"(d[38]), "+f"(d[39]), "+f"(d[40]), "+f"(d[41]), "+f"(d[42]), "+f"(d[43]), "+f"(d[44]), "+f"(d[45]), "+f"(d[46]), "+f"(d[47]), "+f"(d[48]), "+f"(d[49]), "+f"(d[50]), "+f"(d[51]), "+f"(d[52]), "+f"(d[53]), "+f"(d[54]), "+f"(d[55]), "+f"(d[56]), "+f"(d[57]), "+f"(d[58]), "+f"(d[59]), "+f"(d[60]), "+f"(d[61]), "+f"(d[62]), "+f"(d[63])
    : "r"(a0), "r"(a1), "r"(a2), "r"(a3), "l"(db), "r"(sc));
}
__device__ __forceinline__ void wgmma_rs_n112(float (&d)[56], uint32_t a0, uint32_t a1, uint32_t a2, uint32_t a3, uint64_t db, int sc) {
  asm volatile("{\n.reg .pred p;\nsetp.ne.b32 p, %61, 0;\n"
    "wgmma.mma_async.sync.aligned.m64n112k16.f32.bf16.bf16 {%0, %1, %2, %3, %4, %5, %6, %7, %8, %9, %10, %11, %12, %13, %14, %15, %16, %17, %18, %19, %20, %21, %22, %23, %24, %25, %26, %27, %28, %29, %30, %31, %32, %33, %34, %35, %36, %37, %38, %39, %40, %41, %42, %43, %44, %45, %46, %47, %48, %49, %50, %51, %52, %53, %54, %55}, {%56, %57, %58, %59}, %60, p, 1, 1, 1;\n}\n"
    : "+f"(d[0]), "+f"(d[1]), "+f"(d[2]), "+f"(d[3]), "+f"(d[4]), "+f"(d[5]), "+f"(d[6]), "+f"(d[7]), "+f"(d[8]), "+f"(d[9]), "+f"(d[10]), "+f"(d[11]), "+f"(d[12]), "+f"(d[13]), "+f"(d[14]), "+f"(d[15]), "+f"(d[16]), "+f"(d[17]), "+f"(d[18]), "+f"(d[19]), "+f"(d[20]), "+f"(d[21]), "+f"(d[22]), "+f"(d[23]), "+f"(d[24]), "+f"(d[25]), "+f"(d[26]), "+f"(d[27]), "+f"(d[28]), "+f"(d[29]), "+f"(d[30]), "+f"(d[31]), "+f"(d[32]), "+f"(d[33]), "+f"(d[34]), "+f"(d[35]), "+f"(d[36]), "+f"(d[37]), "+f"(d[38]), "+f"(d[39]), "+f"(d[40]), "+f"(d[41]), "+f"(d[42]), "+f"(d[43]), "+f"(d[44]), "+f"(d[45]), "+f"(d[46]), "+f"(d[47]), "+f"(d[48]), "+f"(d[49]), "+f"(d[50]), "+f"(d[51]), "+f"(d[52]), "+f"(d[53]), "+f"(d[54]), "+f"(d[55])
    : "r"(a0), "r"(a1), "r"(a2), "r"(a3), "l"(db), "r"(sc));
}

struct cplx { float re, im; };
__device__ __forceinline__ cplx cmul(cplx a, cplx b) {
  cplx r; r.re = a.re * b.re - a.im * b.im; r.im = a.re * b.im + a.im * b.re; return r;
}
__device__ __forceinline__ cplx zpow_acc(float a2, float bt, float c) {
  float mag = ex2f(a2 * c);
  float tr = bt * c;
  tr -= rintf(tr);
  float ang = tr * 6.283185307179586f;
  cplx r; r.re = mag * __cosf(ang); r.im = mag * __sinf(ang); return r;
}

constexpr int SB_TAB  = 0;
constexpr int SB_WREG = 7168;
constexpr int UZ = 40;
constexpr int SB_U    = 4 * SB_WREG;
constexpr int SB_KV   = SB_U + 172 * 36;
constexpr int SB_TOTAL = (SB_KV + 644 * 4 + 127) / 128 * 128;
constexpr int SB_F3   = 0;
constexpr int SB_F2   = 1792;
constexpr int SB_Y    = 4096;
constexpr int SB_KD   = SB_Y;
constexpr int SB_KDO  = SB_KD + 2240;
constexpr int FR_LN = 4 * SB_TOTAL;
constexpr int FR_CS = (FR_LN + LN_SMEM + 127) / 128 * 128;
constexpr int FR_X = FR_CS + CS_SMEM;
constexpr int FRONT_SMEM = FR_X + 16384;
constexpr int FR_BAR = 229120 + 320;

__device__ __forceinline__ int rowaddr(int r) { return 32 * r + 16 * (r >> 2); }
struct hc { __half2 re, im; };
__device__ __forceinline__ hc bcast(cplx a) { hc r; r.re = __float2half2_rn(a.re); r.im = __float2half2_rn(a.im); return r; }
__device__ __forceinline__ hc hmul(hc v, hc s) {
  hc r;
  r.re = __hfma2(v.re, s.re, __hneg2(__hmul2(v.im, s.im)));
  r.im = __hfma2(v.re, s.im, __hmul2(v.im, s.re));
  return r;
}
__device__ __forceinline__ uint32_t h2u(__half2 h) { return *reinterpret_cast<uint32_t*>(&h); }
__device__ __forceinline__ void gen8(unsigned char* p, cplx s, cplx r1, hc r1sq, hc r2) {
  const cplx v1 = cmul(s, r1);
  hc p0; p0.re = __floats2half2_rn(s.re, v1.re); p0.im = __floats2half2_rn(s.im, v1.im);
  const hc p1 = hmul(p0, r1sq), p2 = hmul(p0, r2), p3 = hmul(p1, r2);
  *reinterpret_cast<uint4*>(p) = make_uint4(h2u(p0.re), h2u(p1.re), h2u(p2.re), h2u(p3.re));
  *reinterpret_cast<uint4*>(p + 8 * 112) = make_uint4(h2u(p0.im), h2u(p1.im), h2u(p2.im), h2u(p3.im));
}
__device__ __forceinline__ cplx csq(cplx a) { cplx r; r.re = a.re * a.re - a.im * a.im; r.im = 2.f * a.re * a.im; return r; }
__device__ __forceinline__ cplx cconj(cplx a) { a.im = -a.im; return a; }
__device__ __forceinline__ uint2 lds64(uint32_t a) { uint2 r; asm volatile("ld.shared.v2.u32 {%0,%1}, [%2];" : "=r"(r.x), "=r"(r.y) : "r"(a)); return r; }

__device__ __forceinline__ void mlp_bar_init(uint32_t base) {
  if ((threadIdx.x & 31) == 0 && (threadIdx.x >> 7) == 1) {
#pragma unroll 1
    for (int b = (threadIdx.x >> 5) - 4; b < 36; b += 4) mbar_init(base + 8 * b, ((b >= 10 && b < 13) || b == 28 || b >= 32) ? 2 : 1);
    asm volatile("fence.mbarrier_init.release.cluster;" ::: "memory");
  }
  __syncwarp();
}

__device__ __forceinline__ void front_phase(Scratch* __restrict__ S, const bf16* __restrict__ Are, const bf16* __restrict__ Aim,
                                             const bf16* __restrict__ Bre, const bf16* __restrict__ Bim,
                                             const bf16* __restrict__ Cre, const bf16* __restrict__ Cim,
                                             const bf16* __restrict__ log_dt, const bf16* __restrict__ Dskip,
                                             const bf16* __restrict__ x, const bf16* __restrict__ wg,
                                             const bf16* __restrict__ wu, const bf16* __restrict__ wd,
                                             const CUtensorMap& tmU, const CUtensorMap& tmX) {
  extern __shared__ __align__(1024) unsigned char smem_all[];
  const int sub = threadIdx.x >> 7;
  const int tid = threadIdx.x & 127, lane = tid & 31;
  const int bar = 1 + sub;
  unsigned char* sm = smem_all + sub * SB_TOTAL;
  const uint32_t sbase = smem_u32(sm);
  const int w = ((tid >> 5) + sub) & 3;
  const int g = lane >> 2, t = lane & 3;
  const bool upper = threadIdx.x >= 256;
  const int hbar = upper ? 14 : 13;
  const bool do_ln = upper && blockIdx.x < 128;
  if (do_ln) ln1_load(x, blockIdx.x, smem_all + FR_LN);
  if (blockIdx.x >= 112) {
    mlp_bar_init(smem_u32(smem_all) + FR_BAR - 320);
    if (do_ln) ln1_tile(S, blockIdx.x, smem_all + FR_LN);
    if (upper) named_bar(hbar, 256);
    const int t0 = (blockIdx.x - 112) + (upper ? 20 : 0);
    unsigned char* cs = smem_all + (upper ? 3 * CS_SMEM : 0);
#pragma unroll
    for (int i = 0; i < 3; i++)
      if (t0 + 40 * i < 112) colsum_load(wg, wu, t0 + 40 * i, cs + i * CS_SMEM);
    for (int i = (blockIdx.x - 112) * 512 + threadIdx.x; i < FF * DM * 2 / 128; i += 20 * 512)
      asm volatile("prefetch.global.L2 [%0];" ::"l"(reinterpret_cast<const char*>(wd) + (size_t)i * 128));
    cp_async_wait_all();
    named_bar(hbar, 256);
#pragma unroll
    for (int i = 0; i < 3; i++)
      if (t0 + 40 * i < 112) colsum_reduce(cs + i * CS_SMEM);
    named_bar(hbar, 256);
    const int wi = (threadIdx.x >> 5) & 7;
    if (wi < 3 && t0 + 40 * wi < 112) colsum_store(S, t0 + 40 * wi, cs + wi * CS_SMEM);
    named_bar(hbar, 256);
    if ((threadIdx.x & 255) == 0) {
      asm volatile("fence.acq_rel.gpu;" ::: "memory");
      asm volatile("red.relaxed.gpu.global.add.u32 [%0], 1;" ::"l"(&S->cnt[8]) : "memory");
    }
    return;
  }
  const int d = blockIdx.x * 4 + sub;
  if ((threadIdx.x & 255) == 0) mbar_init(smem_u32(smem_all) + FR_BAR + (upper ? 8 : 0), 1);
  const int pidx = (d * NM + 64 * w) / 2 + lane;
  const uint32_t pAre = __ldg(reinterpret_cast<const uint32_t*>(Are) + pidx), pAim = __ldg(reinterpret_cast<const uint32_t*>(Aim) + pidx);
  const uint32_t pBre = __ldg(reinterpret_cast<const uint32_t*>(Bre) + pidx), pBim = __ldg(reinterpret_cast<const uint32_t*>(Bim) + pidx);
  const uint32_t pCre = __ldg(reinterpret_cast<const uint32_t*>(Cre) + pidx), pCim = __ldg(reinterpret_cast<const uint32_t*>(Cim) + pidx);
  const bf16 ldt_raw = log_dt[d];
  mlp_bar_init(smem_u32(smem_all) + FR_BAR - 320);
  const float dt = bf16r(expf(__bfloat162float(ldt_raw)));
  const uint32_t dsk2 = (uint32_t)__bfloat16_as_ushort(Dskip[d]) * 0x10001u;
  if (upper) ln1_tile(S, blockIdx.x, smem_all + FR_LN);
  if (tid < 90) *reinterpret_cast<uint4*>(sm + SB_U + tid * 16) = make_uint4(0, 0, 0, 0);
  if (tid >= 96 && tid < 105) *reinterpret_cast<uint4*>(sm + SB_U + 168 * 36 + (tid - 96) * 16) = make_uint4(0, 0, 0, 0);
  float w0re, w0im, w1re, w1im;
  {
    const float br0 = dt * bflo(pBre), bi0 = dt * bflo(pBim), br1 = dt * bfhi(pBre), bi1 = dt * bfhi(pBim);
    w0re = bflo(pCre) * br0 - bflo(pCim) * bi0; w0im = bflo(pCre) * bi0 + bflo(pCim) * br0;
    w1re = bfhi(pCre) * br1 - bfhi(pCim) * bi1; w1im = bfhi(pCre) * bi1 + bfhi(pCim) * br1;
  }
  float mx = fmaxf(fmaxf(fabsf(w0re), fabsf(w0im)), fmaxf(fabsf(w1re), fabsf(w1im)));
#pragma unroll
  for (int o = 16; o > 0; o >>= 1) mx = fmaxf(mx, __shfl_xor_sync(0xffffffffu, mx, o));
  int ex = (__float_as_uint(mx) >> 23) & 0xff;
  ex = min(max(ex, 1), 252);
  const float scale = __uint_as_float((uint32_t)(253 - ex) << 23);
  const float inv_scale = __uint_as_float((uint32_t)(ex + 1) << 23);

  float acc[5][4];
#pragma unroll
  for (int i = 0; i < 5; i++) { acc[i][0] = acc[i][1] = acc[i][2] = acc[i][3] = 0.f; }
  float k2048 = 0.f;
  unsigned char* tabw = sm + SB_TAB + w * SB_WREG;
  const uint32_t ldA = sbase + SB_TAB + w * SB_WREG + ((lane & 7) + 8 * ((lane >> 4) & 1)) * 112 + ((lane >> 3) & 1) * 16;
  const uint32_t ldB = sbase + SB_TAB + w * SB_WREG + ((lane & 7) + 8 * ((lane >> 3) & 1)) * 112 + 32 + (lane >> 4) * 16;
#pragma unroll 1
  for (int r = 0; r < 2; r++) {
    {
      const float a2 = dt * (r ? bfhi(pAre) : bflo(pAre)) * 1.4426950408889634f;
      const float bt = dt * (r ? bfhi(pAim) : bflo(pAim)) * 0.15915494309189535f;
      cplx W; W.re = (r ? w1re : w0re) * scale; W.im = -(r ? w1im : w0im) * scale;
      unsigned char* rec = tabw + ((lane >> 3) * 16 + (lane & 7)) * 112;
      const cplx y1 = zpow_acc(a2, -bt, 1.f), y128 = zpow_acc(a2, -bt, 128.f);
      const cplx y2 = csq(y1), y4 = csq(y2), z8 = cconj(csq(y4));
      const cplx z16 = csq(z8), z32 = csq(z16), z64 = csq(z32);
      const cplx y256 = csq(y128), y512 = csq(y256), y1024 = csq(y512);
      cplx one; one.re = 1.f; one.im = 0.f;
      const hc h16 = bcast(z16), h32 = bcast(z32), h2 = bcast(y2), h4 = bcast(y4);
      const hc h128 = bcast(y128), h256 = bcast(y256), h512 = bcast(y512);
      gen8(rec, one, z8, h16, h32);
      gen8(rec + 16, z64, z8, h16, h32);
      gen8(rec + 32, W, y1, h2, h4);
      gen8(rec + 48, cmul(W, y128), y1, h2, h4);
      gen8(rec + 64, cmul(W, y256), y2, h4, h128);
      gen8(rec + 80, cmul(W, y512), y128, h256, h4);
      const cplx w1024 = cmul(W, y1024);
      gen8(rec + 96, w1024, y128, h256, h512);
      k2048 += w1024.re * y1024.re - w1024.im * y1024.im;
    }
    __syncwarp();
#pragma unroll
    for (int ks = 0; ks < 4; ks++) {
      uint32_t a0, a1, a2, a3, b0, b1, b2, b3;
      ldsm_x4_t(ldA + ks * 1792, a0, a1, a2, a3);
      ldsm_x4_t(ldB + ks * 1792, b0, b1, b2, b3);
      mma_f16(acc[0], a0, a1, a2, a3, b0, b1);
      mma_f16(acc[1], a0, a1, a2, a3, b2, b3);
      ldsm_x4_t(ldB + ks * 1792 + 32, b0, b1, b2, b3);
      mma_f16(acc[2], a0, a1, a2, a3, b0, b1);
      mma_f16(acc[3], a0, a1, a2, a3, b2, b3);
      ldsm_x2_t(ldB + ks * 1792 + 64, b0, b1);
      mma_f16(acc[4], a0, a1, a2, a3, b0, b1);
    }
    __syncwarp();
  }
  {
    float* red = reinterpret_cast<float*>(tabw);
#pragma unroll
    for (int hr = 0; hr < 2; hr++) {
      const int row = g + 8 * hr;
      *reinterpret_cast<float2*>(red + 8 * row + 2 * t) = make_float2(acc[0][2 * hr] * inv_scale, acc[0][2 * hr + 1] * inv_scale);
      *reinterpret_cast<float2*>(red + 128 + 8 * row + 2 * t) = make_float2(acc[1][2 * hr] * inv_scale, acc[1][2 * hr + 1] * inv_scale);
      *reinterpret_cast<float2*>(red + 256 + 64 * (t >> 1) + 2 * (t & 1) + 4 * row) = make_float2(acc[2][2 * hr] * inv_scale, acc[2][2 * hr + 1] * inv_scale);
      red[384 + 64 * (t & 1) + (t >> 1) + 2 * row] = acc[3][2 * hr] * inv_scale;
      red[384 + 64 * (t & 1) + 32 + (t >> 1) + 2 * row] = acc[3][2 * hr + 1] * inv_scale;
      red[512 + 32 * t + row] = acc[4][2 * hr] * inv_scale;
      red[512 + 32 * t + 16 + row] = acc[4][2 * hr + 1] * inv_scale;
    }
#pragma unroll
    for (int o = 16; o > 0; o >>= 1) k2048 += __shfl_xor_sync(0xffffffffu, k2048, o);
    if (lane == 0) red[640] = k2048 * inv_scale;
  }
  const uint32_t ubar = smem_u32(smem_all) + FR_BAR + (upper ? 8 : 0);
  const int ustg = upper ? FR_LN : FR_CS;
  if ((threadIdx.x & 255) == 0) {
    flag_wait(&S->cnt[7], (__ldcg(&S->epoch) + 1u) * 128u);
    asm volatile("fence.proxy.async.global;" ::: "memory");
    mbar_expect(ubar, 16384);
    tma2d(smem_u32(smem_all) + ustg, &tmU, ubar, (blockIdx.x * 4 + (sub & 2)) * 16, 0);
    tma2d(smem_u32(smem_all) + FR_X + (upper ? 8192 : 0), &tmX, ubar, (blockIdx.x * 4 + (sub & 2)) * 16, 0);
  }
  __syncwarp();
  named_bar(bar, 128);
  float* Kv = reinterpret_cast<float*>(sm + SB_KV);
  {
    const float* r0 = reinterpret_cast<const float*>(sm + SB_TAB);
    constexpr int WS = SB_WREG / 4;
    const float4 a = *reinterpret_cast<const float4*>(r0 + 4 * tid), b = *reinterpret_cast<const float4*>(r0 + WS + 4 * tid);
    const float4 c = *reinterpret_cast<const float4*>(r0 + 2 * WS + 4 * tid), e = *reinterpret_cast<const float4*>(r0 + 3 * WS + 4 * tid);
    *reinterpret_cast<float4*>(Kv + 4 * tid) =
        make_float4((a.x + b.x) + (c.x + e.x), (a.y + b.y) + (c.y + e.y), (a.z + b.z) + (c.z + e.z), (a.w + b.w) + (c.w + e.w));
    const int i = 512 + tid;
    Kv[i] = (r0[i] + r0[WS + i]) + (r0[2 * WS + i] + r0[3 * WS + i]);
    if (tid == 0) Kv[640] = (r0[640] + r0[WS + 640]) + (r0[2 * WS + 640] + r0[3 * WS + 640]);
  }
  named_bar(bar, 128);
  {
    auto tap_idx = [](int j) { const int m = j >> 1; const int r = (j & 1) ? m + (m & 1) : m; return min(max(j < 256 ? j : 128 + r, 0), 640); };
    float kd[3][3], f3[3], f2[3];
#pragma unroll
    for (int it = 0; it < 3; it++) {
      const int j = 528 - 2 * (tid + 128 * it);
#pragma unroll
      for (int e = 0; e < 3; e++) kd[it][e] = Kv[tap_idx(j + 1 - e)];
    }
    const int fa = tid >= 48, xa = tid - 48 * fa, ja = 144 - 2 * xa;
    const int fb = tid >> 6, xb = tid & 63, jb = 160 - 2 * xb;
#pragma unroll
    for (int e = 0; e < 3; e++) {
      f3[e] = Kv[min(max(384 + fa + 2 * (ja + 1 - e), 0), 640)];
      f2[e] = Kv[min(256 + fb + 2 * (jb + 1 - e), 640)];
    }
    const float k512 = Kv[384];
    uint32_t* ee = reinterpret_cast<uint32_t*>(sm + SB_KD);
#pragma unroll
    for (int it = 0; it < 3; it++) {
      const int x = tid + 128 * it, j = 528 - 2 * x;
      const float k0 = (j >= -1 && j <= 508) ? kd[it][0] : 0.f;
      float k1 = (j >= 0 && j <= 510) ? kd[it][1] : 0.f;
      const float k2 = (j >= 1 && j <= 510) ? kd[it][2] : 0.f;
      if (j == 510) k1 -= k512;
      const uint32_t we = pack_bf16(k1, k2), wo = pack_bf16(k0, k1);
      if (x < 272) { ee[2 * x] = we; ee[560 + 2 * x] = wo; }
      if (x < 272 && x >= 4) { ee[2 * x - 7] = we; ee[560 + 2 * x - 7] = wo; }
    }
    {
      const int hi = 128 - fa;
      const float k0 = (ja + 1 >= 64 && ja + 1 <= hi) ? f3[0] : 0.f, k1 = (ja >= 64 && ja <= hi) ? f3[1] : 0.f;
      const float k2 = (ja - 1 >= 64 && ja - 1 <= hi) ? f3[2] : 0.f;
      const uint32_t we = pack_bf16(k1, k2), wo = pack_bf16(k0, k1);
      uint32_t* p = reinterpret_cast<uint32_t*>(sm + SB_F3) + fa * 224;
      if (tid < 96) { p[2 * xa] = we; p[112 + 2 * xa] = wo; }
      if (tid < 96 && xa < 44) { p[2 * xa + 9] = we; p[112 + 2 * xa + 9] = wo; }
    }
    {
      const float k0 = (jb + 1 >= 64 && jb + 1 <= 127) ? f2[0] : 0.f, k1 = (jb >= 64 && jb <= 127) ? f2[1] : 0.f;
      const float k2 = (jb - 1 >= 64 && jb - 1 <= 127) ? f2[2] : 0.f;
      const uint32_t we = pack_bf16(k1, k2), wo = pack_bf16(k0, k1);
      uint32_t* p = reinterpret_cast<uint32_t*>(sm + SB_F2) + fb * 288;
      p[2 * xb] = we; p[144 + 2 * xb] = wo;
      p[2 * xb + 17] = we; p[144 + 2 * xb + 17] = wo;
    }
  }
  const float k1024 = Kv[512];
  named_bar(hbar, 256);
  mbar_wait(ubar, 0);
#pragma unroll
  for (int k = 0; k < 2; k++) {
    const int c = tid + 128 * k;
    *reinterpret_cast<uint4*>(sm + SB_U + rowaddr((c >> 1) + UZ) + (c & 1) * 16) =
        *reinterpret_cast<const uint4*>(smem_all + ustg + (c >> 1) * 64 + (sub & 1) * 32 + (c & 1) * 16);
  }
  named_bar(hbar, 256);
  const int krow = (lane & 7) + 8 * ((lane >> 3) & 1);
  if (w < 2) {
    float acd[4][2][4];
#pragma unroll
    for (int c = 0; c < 4; c++)
#pragma unroll
      for (int i = 0; i < 2; i++)
#pragma unroll
        for (int e = 0; e < 4; e++) acd[c][i][e] = 0.f;
    const uint32_t aQ = sbase + SB_U + rowaddr(UZ + 64 * w + 4 * krow) + (lane >> 4) * 16;
    const uint32_t pb = sbase + ((g & 1) ? SB_KDO + ((529 - g) / 2 + t) * 8 : SB_KD + ((528 - g) / 2 + t) * 8);
    uint32_t Q[36][4];
#define QOFF(j) (32 * (j) + 16 * (((j) + 64) / 4 - 16))
#pragma unroll
    for (int n = 0; n < 5; n++) ldsm_x4(aQ + QOFF(3 - n), Q[n][0], Q[n][1], Q[n][2], Q[n][3]);
#pragma unroll
    for (int q = 0; q < 33; q++) {
      if (q + 5 < 36) ldsm_x4(aQ + QOFF(3 - (q + 5)), Q[q + 5][0], Q[q + 5][1], Q[q + 5][2], Q[q + 5][3]);
      const uint2 e0 = lds64(pb - 32 * (2 * q));
      const uint2 e1 = lds64(pb - 32 * (2 * q + 1));
#pragma unroll
      for (int c = 0; c < 4; c++) {
        mma_bf16(acd[c][0], Q[3 - c + q][0], Q[3 - c + q][1], Q[3 - c + q][2], Q[3 - c + q][3], e0.x, e0.y);
        mma_bf16(acd[c][1], Q[3 - c + q][0], Q[3 - c + q][1], Q[3 - c + q][2], Q[3 - c + q][3], e1.x, e1.y);
      }
    }
#undef QOFF
    const int yl = (64 * (16 * w + g) + 2 * t + 16 * (g & 1) + 8 * ((g >> 1) & 1)) * 4;
    unsigned char* yb = sm + SB_Y + 8192;
#pragma unroll
    for (int c = 0; c < 4; c++)
#pragma unroll
      for (int nu = 0; nu < 2; nu++)
#pragma unroll
        for (int hr = 0; hr < 2; hr++)
          *reinterpret_cast<float2*>(yb + ((yl ^ ((16 * c + 8 * (nu ^ (c >> 1))) * 4)) + hr * 2048)) = make_float2(acd[c][nu][2 * hr], acd[c][nu][2 * hr + 1]);
  } else {
    const int yl = (16 * (g ^ ((g >> 2) & 1)) + 2 * t + 8 * ((g >> 1) & 1)) * 4;
    if (w == 2) {
      float ac[7][2][4];
#pragma unroll
      for (int T = 0; T < 7; T++)
#pragma unroll
        for (int i = 0; i < 2; i++)
#pragma unroll
          for (int e = 0; e < 4; e++) ac[T][i][e] = 0.f;
      uint32_t BA[2][4];
#pragma unroll
      for (int ks = 0; ks < 2; ks++)
#pragma unroll
        for (int r = 0; r < 4; r++) {
          uint32_t v = 0;
#pragma unroll
          for (int e = 0; e < 2; e++) {
            const int dlt = (2 * t + e + 8 * (r >> 1) + 16 * ks - 8) - g;
            const bool on = (r & 1) ? (dlt >= -5 && dlt <= -3) : (dlt >= -2 && dlt <= 2);
            v |= on ? (0x3f80u << (16 * e)) : 0u;
          }
          BA[ks][r] = v;
        }
      const int chl = 2 * UZ + (lane & 7) + (lane >> 3) - 1;
      const uint32_t ub = sbase + SB_U + rowaddr(chl >> 1) + (chl & 1) * 16;
      const uint32_t fb = sbase + SB_F2 + (80 - (g - t)) * 8;
#pragma unroll
      for (int sp = 0; sp < 2; sp++) {
        uint32_t bb[2][7][2];
#pragma unroll
        for (int i = 0; i < 7 - sp; i++) {
          const int beta = 11 - sp - 2 * i;
#pragma unroll
          for (int o = 0; o < 2; o++) {
            uint32_t u0, u1, u2, u3;
            ldsm_x4(ub + (2 * beta + o) * 144, u0, u1, u2, u3);
            float z[4] = {0.f, 0.f, 0.f, 0.f};
            mma_bf16(z, BA[0][0], BA[0][1], BA[0][2], BA[0][3], u0, u1);
            mma_bf16(z, BA[1][0], BA[1][1], BA[1][2], BA[1][3], u2, u3);
            bb[0][i][o] = pack_bf16(z[0], z[1]);
            bb[1][i][o] = pack_bf16(z[2], z[3]);
          }
        }
#pragma unroll
        for (int f = 0; f < 2; f++) {
#pragma unroll
          for (int k = 0; k < 3; k++) {
#pragma unroll
            for (int nu = 0; nu < 2; nu++) {
              const uint2 A01 = lds64(fb + f * 1152 + nu * 576 - 32 * (6 + 2 * (2 * k + sp)));
              const uint2 A23 = lds64(fb + f * 1152 + nu * 576 - 32 * (5 + 2 * (2 * k + sp)));
#pragma unroll
              for (int i = 0; i < 7 - sp; i++) {
                const int T = 7 - i + k;
                if (T <= 7) mma_bf16(ac[T - 1][nu], A01.x, A01.y, A23.x, A23.y, bb[f][i][0], bb[f][i][1]);
              }
            }
          }
        }
      }
      named_bar(5 + bar, 96);
      unsigned char* yb = sm + SB_Y;
#pragma unroll
      for (int T = 0; T <= 7; T++)
#pragma unroll
        for (int nu = 0; nu < 2; nu++)
#pragma unroll
          for (int hr = 0; hr < 2; hr++)
            *reinterpret_cast<float2*>(yb + ((yl ^ ((8 * (nu ^ hr)) * 4)) + (16 * T + 8 * hr) * 64)) =
                T ? make_float2(ac[T ? T - 1 : 0][nu][2 * hr], ac[T ? T - 1 : 0][nu][2 * hr + 1]) : make_float2(0.f, 0.f);
    } else {
      float ac[5][2][4];
#pragma unroll
      for (int T = 0; T < 5; T++)
#pragma unroll
        for (int i = 0; i < 2; i++)
#pragma unroll
          for (int e = 0; e < 4; e++) ac[T][i][e] = 0.f;
      const uint32_t fb = sbase + SB_F3 + ((g & 1) ? 448 + ((145 - g) / 2 + t) * 8 : ((144 - g) / 2 + t) * 8);
      uint32_t ur[3];
#pragma unroll
      for (int sg = 0; sg < 3; sg++) ur[sg] = sbase + SB_U + rowaddr(UZ + (lane & 7) + 8 * (lane >> 4) + sg - 1) + ((lane >> 3) & 1) * 16;
#pragma unroll 1
      for (int f = 0; f < 2; f++) {
        uint32_t BA[3][4];
        const int lo = f ? -11 : -4, hi = f ? -5 : 4;
#pragma unroll
        for (int sg = 0; sg < 3; sg++)
#pragma unroll
          for (int r = 0; r < 4; r++) {
            uint32_t v = 0;
#pragma unroll
            for (int e = 0; e < 2; e++) {
              const int dlt = (2 * t + e + 8 * (r >> 1) + 16 * (sg - 1)) - (g + 8 * (r & 1));
              v |= (dlt >= lo && dlt <= hi) ? (0x3f80u << (16 * e)) : 0u;
            }
            BA[sg][r] = v;
          }
        uint2 A01[5], A23[5];
#pragma unroll
        for (int s = 0; s < 5; s++) {
          A01[s] = lds64(fb + f * 896 - 32 * (8 + 2 * s));
          A23[s] = lds64(fb + f * 896 - 32 * (7 + 2 * s));
        }
#pragma unroll
        for (int beta = 3; beta >= -1; beta--) {
          float z0[4] = {0.f, 0.f, 0.f, 0.f}, z1[4] = {0.f, 0.f, 0.f, 0.f};
#pragma unroll
          for (int sg = 0; sg < 3; sg++) {
            uint32_t u0, u1, u2, u3;
            ldsm_x4(ur[sg] + beta * 576, u0, u1, u2, u3);
            mma_bf16(z0, BA[sg][0], BA[sg][1], BA[sg][2], BA[sg][3], u0, u1);
            mma_bf16(z1, BA[sg][0], BA[sg][1], BA[sg][2], BA[sg][3], u2, u3);
          }
          const uint32_t b0 = pack_bf16(z0[0], z0[1]), b1 = pack_bf16(z1[0], z1[1]);
          const uint32_t b2 = pack_bf16(z0[2], z0[3]), b3 = pack_bf16(z1[2], z1[3]);
#pragma unroll
          for (int s = 0; s < 5; s++) {
            const int T = beta + 4 + s;
            if (T <= 7) {
              mma_bf16(ac[T - 3][0], A01[s].x, A01[s].y, A23[s].x, A23[s].y, b0, b1);
              mma_bf16(ac[T - 3][1], A01[s].x, A01[s].y, A23[s].x, A23[s].y, b2, b3);
            }
          }
        }
      }
      {
        const uint32_t nk = (uint32_t)__bfloat16_as_ushort(__float2bfloat16_rn(-k1024));
        uint32_t PC[5];
#pragma unroll
        for (int m = 0; m < 5; m++) {
          const int j = 8 * (125 + m) + g - 2 * t;
          PC[m] = ((j == 1020 || j == 1021) ? nk : 0u) | ((j == 1021 || j == 1022) ? (nk << 16) : 0u);
        }
#pragma unroll
        for (int k = 0; k < 2; k++) {
          const uint32_t ab = sbase + SB_U + rowaddr(UZ + 48 - 63 - k + krow) + (lane >> 4) * 16;
#pragma unroll
          for (int T = 3; T <= 7; T++) {
            uint32_t a0, a1, a2, a3;
            ldsm_x4(ab + (T - 3) * 576, a0, a1, a2, a3);
            mma_bf16(ac[T - 3][0], a0, a1, a2, a3, PC[1 + 2 * k], PC[2 * k]);
            mma_bf16(ac[T - 3][1], a0, a1, a2, a3, PC[2 + 2 * k], PC[1 + 2 * k]);
          }
        }
      }
      unsigned char* yb = sm + SB_Y + 16384;
#pragma unroll
      for (int T = 0; T <= 7; T++)
#pragma unroll
        for (int nu = 0; nu < 2; nu++)
#pragma unroll
          for (int hr = 0; hr < 2; hr++)
            *reinterpret_cast<float2*>(yb + ((yl ^ ((8 * (nu ^ hr)) * 4)) + (16 * T + 8 * hr) * 64)) =
                T >= 3 ? make_float2(ac[T >= 3 ? T - 3 : 0][nu][2 * hr], ac[T >= 3 ? T - 3 : 0][nu][2 * hr + 1]) : make_float2(0.f, 0.f);
    }
  }
  if (w < 2) asm volatile("bar.arrive %0, 96;" ::"r"(5 + bar) : "memory");
  named_bar(bar, 128);
  {
    const __nv_bfloat162 ds = *reinterpret_cast<const __nv_bfloat162*>(&dsk2);
    const int r0 = tid >> 2, ch = tid & 3;
    const int yo = (16 * (r0 ^ ((r0 >> 2) & 1)) + ((4 * ch) ^ (8 * (((r0 >> 1) ^ (r0 >> 3)) & 1)))) * 4;
    const int uo = SB_U + rowaddr(r0 + UZ) + ch * 8;
#pragma unroll
    for (int k = 0; k < 4; k++) {
      const float4 a = *reinterpret_cast<const float4*>(sm + SB_Y + yo + k * 2048);
      const float4 b = *reinterpret_cast<const float4*>(sm + SB_Y + 8192 + yo + k * 2048);
      const float4 c = *reinterpret_cast<const float4*>(sm + SB_Y + 16384 + yo + k * 2048);
      const uint2 uw = *reinterpret_cast<const uint2*>(sm + uo + k * 1152);
      const uint2 xw = *reinterpret_cast<const uint2*>(smem_all + FR_X + (sub >> 1) * 8192 + r0 * 64 + (sub & 1) * 32 + ch * 8 + k * 2048);
      const uint32_t y0 = pack_bf16(b.x + (a.x + c.x), b.y + (a.y + c.y)), y1 = pack_bf16(b.z + (a.z + c.z), b.w + (a.w + c.w));
      const __nv_bfloat162 h0 = __hadd2_rn(*reinterpret_cast<const __nv_bfloat162*>(&xw.x),
          __hadd2_rn(*reinterpret_cast<const __nv_bfloat162*>(&y0), __hmul2_rn(*reinterpret_cast<const __nv_bfloat162*>(&uw.x), ds)));
      const __nv_bfloat162 h1 = __hadd2_rn(*reinterpret_cast<const __nv_bfloat162*>(&xw.y),
          __hadd2_rn(*reinterpret_cast<const __nv_bfloat162*>(&y1), __hmul2_rn(*reinterpret_cast<const __nv_bfloat162*>(&uw.y), ds)));
      *reinterpret_cast<uint2*>(S->hT + (size_t)d * SEQ + tid * 4 + k * 512) =
          make_uint2(*reinterpret_cast<const uint32_t*>(&h0), *reinterpret_cast<const uint32_t*>(&h1));
    }
  }
  if (threadIdx.x < 480) {
    asm volatile("bar.arrive 11, 512;" ::: "memory");
  } else {
    fence_async();
    asm volatile("bar.arrive 15, 512;" ::: "memory");
    named_bar(11, 512);
    if (lane == 0) {
      asm volatile("fence.acq_rel.gpu;" ::: "memory");
      asm volatile("red.relaxed.gpu.global.add.u32 [%0], 1;" ::"l"(&S->cnt[blockIdx.x >> 4]) : "memory");
    }
    __syncwarp();
  }
}

constexpr int M_A     = 0;
constexpr int M_W     = 7 * 16384;
constexpr int M_XB    = M_W + 3 * 32768;
constexpr int M_CS    = M_XB + 14336;
constexpr int M_BAR   = M_CS + 1792;
constexpr int M_TOTAL = M_BAR + 384;

template <int NCB, int NA>
__device__ __forceinline__ void g1_pack(const float (&acc)[NA], uint32_t* pk, const float* cs, float mb0, float mb1, int lane) {
  const int t = lane & 3;
#pragma unroll
  for (int cb = 0; cb < NCB; cb++) {
    const float2 sc = *reinterpret_cast<const float2*>(cs + cb * 8 + 2 * t);
    pk[2 * cb]     = pack_bf16(fmaf(-mb0, sc.x, acc[4 * cb + 0]), fmaf(-mb0, sc.y, acc[4 * cb + 1]));
    pk[2 * cb + 1] = pack_bf16(fmaf(-mb1, sc.x, acc[4 * cb + 2]), fmaf(-mb1, sc.y, acc[4 * cb + 3]));
  }
}
__device__ __forceinline__ uint32_t glu2(uint32_t gw, uint32_t uw, float hr) {
  float t0, t1;
  asm("tanh.approx.f32 %0, %1;" : "=f"(t0) : "f"(bflo(gw) * hr));
  asm("tanh.approx.f32 %0, %1;" : "=f"(t1) : "f"(bfhi(gw) * hr));
  return pack_bf16(fmaf(t0, hr, hr) * bflo(uw), fmaf(t1, hr, hr) * bfhi(uw));
}
__device__ __forceinline__ uint32_t w2_slot(int j, int kp) {
  const int sl = j % 10;
  if (sl < 6) return M_W + ((sl >> 1) + 2) % 3 * 32768 + (sl & 1) * 16384;
  const int i = sl - 6;
  return M_A + (i + (i >= kp ? 3 : 0)) * 16384;
}

__global__ void __cluster_dims__(2, 1, 1) __launch_bounds__(512, 1)
k_all(Scratch* __restrict__ S, const bf16* __restrict__ Are, const bf16* __restrict__ Aim, const bf16* __restrict__ Bre, const bf16* __restrict__ Bim,
      const bf16* __restrict__ Cre, const bf16* __restrict__ Cim, const bf16* __restrict__ log_dt, const bf16* __restrict__ Dskip,
      const bf16* __restrict__ x, const bf16* __restrict__ wgp, const bf16* __restrict__ wup, const bf16* __restrict__ wdp,
      const __grid_constant__ CUtensorMap tmLu, const __grid_constant__ CUtensorMap tmLx,
      const __grid_constant__ CUtensorMap tmA, const __grid_constant__ CUtensorMap tmG,
      const __grid_constant__ CUtensorMap tmU, const __grid_constant__ CUtensorMap tmD, bf16* __restrict__ out) {
  extern __shared__ __align__(1024) unsigned char smem[];
  const uint32_t sb = smem_u32(smem);
  const int tid = threadIdx.x, lane = tid & 31, warp = tid >> 5;
  const uint32_t barA = sb + M_BAR, barF = barA + 56, barE = barF + 24, barS = barE + 24;
  const uint32_t barW2 = barS + 8, barAf = barW2 + 112, barX = barAf + 8, barH = barX + 8, barE2 = barH + 16;
  if (sb & 1023) __trap();
  if (tid >= 224 && tid < 230) prefetch_tm(tid == 224 ? &tmG : tid == 225 ? &tmU : tid == 226 ? &tmA : tid == 227 ? &tmD : tid == 228 ? &tmLu : &tmLx);
  __syncwarp();

  front_phase(S, Are, Aim, Bre, Bim, Cre, Cim, log_dt, Dskip, x, wgp, wup, wdp, tmLu, tmLx);

  fence_async();
  if (warp < 15 || blockIdx.x >= 112) named_bar(15, 512);
  const uint32_t rank = blockIdx.x & 1;
  const bool live = blockIdx.x < 128;
  const int pr = live ? blockIdx.x >> 1 : 0;
  const int mt = pr & 15;
  const int fp = pr >> 4;
  const int fj = 4 * rank + fp;
  const int kp = min((112 * fp) >> 6, 4);
  __syncwarp();
  cluster_arrive();

  if (warp >= 8) {
    const unsigned int ep = __ldcg(&S->epoch);
    asm volatile("setmaxnreg.dec.sync.aligned.u32 24;");
    if (!live || warp >= 12) {
      cluster_wait();
      if (warp == 9) { named_bar(2, 288); named_bar(3, 288); }
    } else if (warp == 8) {
      if (lane == 0) {
        for (int it = 0; it < 14; it++) {
          const int s = it % 3, rnd = it / 3;
          const bool pb = it >= 7;
          const int kb = pb ? it - 7 : it;
          if (rnd > 0) mbar_wait(barE + 8 * s, (rnd - 1) & 1);
          mbar_expect(barF + 8 * s, 32768);
          const uint32_t dst = sb + M_W + s * 32768;
          const int c0 = 224 * fj + (pb ? 128 : 0);
          tma2d(dst, &tmG, barF + 8 * s, c0, 64 * kb);
          tma2d(dst + 16384, &tmU, barF + 8 * s, c0, 64 * kb);
          tma2d(dst + 8192, &tmG, barF + 8 * s, c0 + 64, 64 * kb);
          tma2d(dst + 24576, &tmU, barF + 8 * s, c0 + 64, 64 * kb);
        }
        for (int j = 0; j < 14; j++) {
          if (j < 6 && !(j & 1)) { const int it = 11 + (j >> 1); mbar_wait(barE + 8 * (it % 3), (it / 3) & 1); }
          if (j == 6) mbar_wait(barAf, 0);
          if (j >= 10) mbar_wait(barE2 + 8 * (j - 10), 0);
          mbar_expect(barW2 + 8 * j, 16384);
          const uint32_t dst = sb + w2_slot(j, kp);
#pragma unroll
          for (int h = 0; h < 2; h++) {
            const int u = 2 * j + h;
            int c, o;
            if (u < 7) { c = 0; o = u; } else if (u < 19) { c = 1 + (u - 7) / 4; o = (u - 7) % 4; } else { c = 1 + (u - 19) / 3; o = 4 + (u - 19) % 3; }
            const int row = (4 * rank + ((fp + c) & 3)) * 224 + 32 * o;
            tma2d(dst + h * 4096, &tmD, barW2 + 8 * j, 112 * fp, row);
            tma2d(dst + 8192 + h * 4096, &tmD, barW2 + 8 * j, 112 * fp + 64, row);
          }
        }
      }
      __syncwarp();
      cluster_wait();
    } else if (warp == 9) {
      if (lane < 7) flag_wait(&S->cnt[lane], (ep + 1u) * 16u);
      __syncwarp();
      cluster_wait();
      if (lane == 0) {
        asm volatile("fence.proxy.async.global;" ::: "memory");
        for (int k = 0; k < 7; k++) {
          mbar_expect(barA + 8 * k, 16384);
          tma3d_mc(sb + M_A + k * 16384 + rank * 8192, &tmA, barA + 8 * k, 0, 64 * k, 2 * mt + rank, (uint16_t)3);
        }
      }
      __syncwarp();
#pragma unroll 1
      for (int p = 0; p < 2; p++) {
        named_bar(2 + p, 288);
        if (lane == 0) {
          asm volatile("fence.acq_rel.gpu;" ::: "memory");
          asm volatile("red.relaxed.gpu.global.add.u32 [%0], 1;" ::"l"(&S->cnt2[(mt * 2 + rank) * 2 + p]) : "memory");
        }
        __syncwarp();
      }
    } else if (warp == 10) {
      cluster_wait();
      if (lane == 0) {
#pragma unroll 1
        for (int p = 0; p < 2; p++) {
          flag_wait(&S->cnt2[(mt * 2 + rank) * 2 + p], (ep + 1u) * 4u);
          mbar_arrive(barH + 8 * p);
        }
      }
    } else {
      if (lane == 0) flag_wait(&S->cnt[8], (ep + 1u) * 40u);
      __syncwarp();
      float* cs = reinterpret_cast<float*>(smem + M_CS);
      for (int i = lane; i < 448; i += 32) cs[i] = __ldcg(&S->cs[(i >= 224 ? FF + i - 224 : i) + fj * 224]);
      __syncwarp();
      if (lane == 0) mbar_arrive(barS);
      __syncwarp();
      cluster_wait();
    }
    __syncwarp();
    cluster_arrive(); cluster_wait();
  } else {
    asm volatile("setmaxnreg.inc.sync.aligned.u32 232;");
    const int wg = warp >> 2, wq = warp & 3;
    const bool elect = (tid & 127) == 0;
    const float* cs = reinterpret_cast<const float*>(smem + M_CS);
#define RELEASE(b) do { if (elect) mbar_arrive(b); } while (0)
#define PUBLISH(p) asm volatile("bar.arrive %0, 288;" ::"r"(2 + (p)) : "memory")
    const int dr = (lane & 7) + 8 * (lane >> 4), tc = 2 * wq + ((lane >> 3) & 1);
    const uint32_t aT = sb + M_A + wg * 8192 + dr * 128 + ((tc ^ (lane & 7)) << 4);
    uint4* hbase = (live ? reinterpret_cast<uint4*>(S->P) : reinterpret_cast<uint4*>(const_cast<bf16*>(wdp))) + (size_t)(mt * 8 * 8 + warp) * (14 * 32) + lane;
    const uint32_t dead = live ? 0u : 1u;
    float mb0, rs0, mb1, rs1;
    uint32_t pkA[64];
    {
      float accA[64], accB[64];
      float s0 = 0.f, q0 = 0.f, s1 = 0.f, q1 = 0.f;
#pragma unroll
      for (int kb = 0; kb < 7; kb++) {
        const int s = kb % 3;
        mbar_wait(barA + 8 * kb, (0) | dead);
        uint32_t af[4][4];
#pragma unroll
        for (int k = 0; k < 4; k++) ldsm_x4_t(aT + kb * 16384 + k * 2048, af[k][0], af[k][1], af[k][2], af[k][3]);
        mbar_wait(barF + 8 * s, ((kb / 3) & 1) | dead);
        const uint64_t db = mk_desc(sb + M_W + s * 32768, 8192, 1024, 1);
        wg_fence();
#pragma unroll
        for (int k = 0; k < 4; k++) {
          wgmma_rs_n128(accA, af[k][0], af[k][1], af[k][2], af[k][3], db + k * 128, (kb | k) != 0);
          wgmma_rs_n128(accB, af[k][0], af[k][1], af[k][2], af[k][3], db + 1024 + k * 128, (kb | k) != 0);
        }
        wg_commit();
        if (kb > 0) { wg_wait<1>(); RELEASE(barE + 8 * ((kb - 1) % 3)); }
#pragma unroll
        for (int k = 0; k < 4; k++) {
#pragma unroll
          for (int h = 0; h < 2; h++) {
            const float a = bflo(af[k][2 * h]), b = bfhi(af[k][2 * h]), c = bflo(af[k][2 * h + 1]), e = bfhi(af[k][2 * h + 1]);
            s0 += a + b; q0 = fmaf(a, a, fmaf(b, b, q0));
            s1 += c + e; q1 = fmaf(c, c, fmaf(e, e, q1));
          }
        }
      }
#pragma unroll
      for (int o = 1; o <= 2; o <<= 1) {
        s0 += __shfl_xor_sync(0xffffffffu, s0, o); q0 += __shfl_xor_sync(0xffffffffu, q0, o);
        s1 += __shfl_xor_sync(0xffffffffu, s1, o); q1 += __shfl_xor_sync(0xffffffffu, q1, o);
      }
      s0 *= (1.0f / DM); s1 *= (1.0f / DM);
      mb0 = bf16r(s0); mb1 = bf16r(s1);
      rs0 = 0.5f * ln_rden(fmaxf(q0 * (1.0f / DM) - s0 * s0, 0.f));
      rs1 = 0.5f * ln_rden(fmaxf(q1 * (1.0f / DM) - s1 * s1, 0.f));
      mbar_wait(barS, (0) | dead);
      wg_wait<0>();
      RELEASE(barE + 0);
      g1_pack<16, 64>(accA, pkA, cs, mb0, mb1, lane);
      g1_pack<16, 64>(accB, pkA + 32, cs + 224, mb0, mb1, lane);
    }
    uint32_t hf[56];
    uint4* hown = live ? hbase + (size_t)fj * (8 * 14 * 32) : reinterpret_cast<uint4*>(S->dummy) + lane;
    {
      float accG[48], accU[48];
#pragma unroll
      for (int kb = 0; kb < 7; kb++) {
        const int it = kb + 7, s = it % 3;
        uint32_t af[4][4];
#pragma unroll
        for (int k = 0; k < 4; k++) ldsm_x4_t(aT + kb * 16384 + k * 2048, af[k][0], af[k][1], af[k][2], af[k][3]);
        mbar_wait(barF + 8 * s, ((it / 3) & 1) | dead);
        const uint64_t db = mk_desc(sb + M_W + s * 32768, 8192, 1024, 1);
        wg_fence();
#pragma unroll
        for (int k = 0; k < 4; k++) {
          wgmma_rs_n96(accG, af[k][0], af[k][1], af[k][2], af[k][3], db + k * 128, (kb | k) != 0);
          wgmma_rs_n96(accU, af[k][0], af[k][1], af[k][2], af[k][3], db + 1024 + k * 128, (kb | k) != 0);
        }
        wg_commit();
        if (kb > 0) { wg_wait<1>(); RELEASE(barE + 8 * ((it - 1) % 3)); }
        if (kb < 4) {
#pragma unroll
          for (int i = 0; i < 8; i++) hf[8 * kb + i] = glu2(pkA[8 * kb + i], pkA[32 + 8 * kb + i], (i & 1) ? rs1 : rs0);
          hown[(2 * kb) * 32] = make_uint4(hf[8 * kb], hf[8 * kb + 1], hf[8 * kb + 2], hf[8 * kb + 3]);
          hown[(2 * kb + 1) * 32] = make_uint4(hf[8 * kb + 4], hf[8 * kb + 5], hf[8 * kb + 6], hf[8 * kb + 7]);
          if (kb == 3) PUBLISH(0);
        }
      }
      wg_wait<0>();
      if (elect) { mbar_arrive(barE + 8 * (13 % 3)); mbar_arrive(barAf); }
#pragma unroll
      for (int cb = 0; cb < 12; cb++) {
        const float2 sg = *reinterpret_cast<const float2*>(cs + 128 + cb * 8 + 2 * (lane & 3));
        const float2 su = *reinterpret_cast<const float2*>(cs + 352 + cb * 8 + 2 * (lane & 3));
#pragma unroll
        for (int h = 0; h < 2; h++) {
          const float mb = h ? mb1 : mb0, hr = h ? rs1 : rs0;
          float t0, t1;
          asm("tanh.approx.f32 %0, %1;" : "=f"(t0) : "f"(fmaf(-mb, sg.x, accG[4 * cb + 2 * h]) * hr));
          asm("tanh.approx.f32 %0, %1;" : "=f"(t1) : "f"(fmaf(-mb, sg.y, accG[4 * cb + 2 * h + 1]) * hr));
          hf[32 + 2 * cb + h] = pack_bf16(fmaf(t0, hr, hr) * fmaf(-mb, su.x, accU[4 * cb + 2 * h]), fmaf(t1, hr, hr) * fmaf(-mb, su.y, accU[4 * cb + 2 * h + 1]));
        }
      }
    }
#pragma unroll
    for (int q = 0; q < 6; q++) hown[(8 + q) * 32] = make_uint4(hf[32 + 4 * q], hf[33 + 4 * q], hf[34 + 4 * q], hf[35 + 4 * q]);
    PUBLISH(1);
    float acc[56];
    const uint4* hc[3];
#pragma unroll
    for (int c = 0; c < 3; c++) hc[c] = hbase + (size_t)(4 * rank + ((fp + c + 1) & 3)) * (8 * 14 * 32);
    auto hsrc = [&](int i) -> const uint4* {
      return i < 38 ? hc[(i - 14) / 8] + ((i - 14) % 8) * 32 : hc[(i - 38) / 6] + (8 + (i - 38) % 6) * 32;
    };
    uint4 hq[6][4];
#pragma unroll
    for (int j = 0; j < 14; j++) {
      if (j == 0) mbar_wait(barH, dead);
      if (j == 7) mbar_wait(barH + 8, dead);
#pragma unroll
      for (int k = 0; k < 4; k++) {
        if (j == 0 && k >= 2) hq[3][k] = __ldcg(hsrc(12 + k));
        if (j <= 4) hq[(j + 4) % 6][k] = __ldcg(hsrc(4 * (j + 4) + k));
        if (j >= 7 && j <= 11) hq[(j + 2) % 6][k] = __ldcg(hsrc(4 * (j + 2) + k));
      }
      mbar_wait(barW2 + 8 * j, (0) | dead);
      const uint64_t db = mk_desc(sb + w2_slot(j, kp), 8192, 1024, 1);
      wg_fence();
#pragma unroll
      for (int k = 0; k < 4; k++) {
        const int i = 4 * j + k;
        if (i < 14) wgmma_rs_n112(acc, hf[4 * i], hf[4 * i + 1], hf[4 * i + 2], hf[4 * i + 3], db + k * 128, i != 0);
        else wgmma_rs_n112(acc, hq[j % 6][k].x, hq[j % 6][k].y, hq[j % 6][k].z, hq[j % 6][k].w, db + k * 128, 1);
      }
      wg_commit();
      if (j > 0) { wg_wait<1>(); if (j <= 4) RELEASE(barE2 + 8 * (j - 1)); }
    }
    wg_wait<0>();
    cluster_wait();
    if (wg != (int)rank) {
      asm volatile("bar.arrive 1, 256;" ::: "memory");
      const uint32_t xd = mapa(sb + M_XB, rank ^ 1) + (tid & 127) * 16;
      const uint32_t xb = mapa(barX, rank ^ 1);
#pragma unroll
      for (int q = 0; q < 7; q++)
        asm volatile("st.async.weak.shared::cluster.mbarrier::complete_tx::bytes.v4.b32 [%0], {%1,%2,%3,%4}, [%5];"
                     ::"r"(xd + q * 2048), "r"(pack_bf16(acc[8 * q], acc[8 * q + 1])), "r"(pack_bf16(acc[8 * q + 2], acc[8 * q + 3])),
                       "r"(pack_bf16(acc[8 * q + 4], acc[8 * q + 5])), "r"(pack_bf16(acc[8 * q + 6], acc[8 * q + 7])), "r"(xb) : "memory");
    } else {
      uint32_t hr[7][4];
      const int d0 = 112 * fp;
#pragma unroll
      for (int q = 0; q < 7; q++) {
        const int dd = d0 + 16 * q;
        ldsm_x4_t(aT + (dd >> 6) * 16384 + (dd & 63) * 128, hr[q][0], hr[q][1], hr[q][2], hr[q][3]);
      }
      if (elect) mbar_expect(barX, 14336);
      mbar_wait(barX, 0);
      const uint32_t stg = sb + M_W + wq * 3840;
      const uint32_t so = stg + ((lane & 7) + 8 * ((lane >> 3) & 1)) * 240 + (lane >> 4) * 16;
      named_bar(1, 256);
#pragma unroll
      for (int q = 0; q < 7; q++) {
        const uint4 v = *reinterpret_cast<const uint4*>(smem + M_XB + q * 2048 + (tid & 127) * 16);
        const uint32_t m0 = pack_bf16(acc[8 * q] + bflo(v.x), acc[8 * q + 1] + bfhi(v.x)), m1 = pack_bf16(acc[8 * q + 2] + bflo(v.y), acc[8 * q + 3] + bfhi(v.y));
        const uint32_t m2 = pack_bf16(acc[8 * q + 4] + bflo(v.z), acc[8 * q + 5] + bfhi(v.z)), m3 = pack_bf16(acc[8 * q + 6] + bflo(v.w), acc[8 * q + 7] + bfhi(v.w));
        stsm_x4(so + q * 32, hadd2_bf16(hr[q][0], m0), hadd2_bf16(hr[q][1], m1), hadd2_bf16(hr[q][2], m2), hadd2_bf16(hr[q][3], m3));
      }
      __syncwarp();
      bf16* o = live ? out + (size_t)(mt * 128 + 64 * wg + 16 * wq) * DM + d0 : S->dummy;
      o += (lane >> 2) * DM + (lane & 3) * 8;
      const unsigned char* sp = smem + M_W + wq * 3840 + (lane >> 2) * 240 + (lane & 3) * 16;
#pragma unroll
      for (int k = 0; k < 8; k++) {
        if ((k & 3) < 3 || (lane & 3) < 2)
          *reinterpret_cast<uint4*>(o + (k >> 2) * 8 * DM + (k & 3) * 32) = *reinterpret_cast<const uint4*>(sp + (k >> 2) * 1920 + (k & 3) * 64);
      }
    }
    if (tid == 0 && live) {
      const unsigned int n = atomicAdd(&S->done, 1u);
      if ((n & 127u) == 127u) atomicAdd(&S->epoch, 1u);
    }
    __syncwarp();
    cluster_arrive(); cluster_wait();
#undef PUBLISH
#undef RELEASE
  }
}

typedef CUresult (*EncFn)(CUtensorMap*, CUtensorMapDataType, cuuint32_t, void*, const cuuint64_t*, const cuuint64_t*,
                          const cuuint32_t*, const cuuint32_t*, CUtensorMapInterleave, CUtensorMapSwizzle,
                          CUtensorMapL2promotion, CUtensorMapFloatOOBfill);

static void make_map(EncFn enc, CUtensorMap* tm, const void* ptr, int rank, const uint64_t* dims, const uint64_t* strides_bytes,
                     const uint32_t* box, CUtensorMapSwizzle swz) {
  cuuint64_t gd[3], gs[2]; cuuint32_t bd[3], es[3] = {1, 1, 1};
  for (int i = 0; i < rank; i++) { gd[i] = dims[i]; bd[i] = box[i]; }
  for (int i = 0; i < rank - 1; i++) gs[i] = strides_bytes[i];
  enc(tm, CU_TENSOR_MAP_DATA_TYPE_BFLOAT16, rank, const_cast<void*>(ptr), gd, gs, bd, es, CU_TENSOR_MAP_INTERLEAVE_NONE, swz,
      CU_TENSOR_MAP_L2_PROMOTION_L2_128B, CU_TENSOR_MAP_FLOAT_OOB_FILL_NONE);
}

template <class K, class... Args>
static void launch_k(K kern, int grid, int block, int smem, bool pdl, Args... args) {
  cudaLaunchConfig_t cfg = {};
  cfg.gridDim = dim3(grid); cfg.blockDim = dim3(block); cfg.dynamicSmemBytes = smem; cfg.stream = cudaStreamPerThread;
  cudaLaunchAttribute at[1];
  at[0].id = cudaLaunchAttributeProgrammaticStreamSerialization;
  at[0].val.programmaticStreamSerializationAllowed = 1;
  cfg.attrs = at; cfg.numAttrs = pdl ? 1 : 0;
  cudaLaunchKernelEx(&cfg, kern, args...);
}

extern "C" void kernel_launch(void* const* d_in, const int* in_sizes, int n_in, void* d_out, int out_size) {
  const bf16* x   = (const bf16*)d_in[0];
  const bf16* Are = (const bf16*)d_in[1];
  const bf16* Aim = (const bf16*)d_in[2];
  const bf16* Bre = (const bf16*)d_in[3];
  const bf16* Bim = (const bf16*)d_in[4];
  const bf16* Cre = (const bf16*)d_in[5];
  const bf16* Cim = (const bf16*)d_in[6];
  const bf16* ldt = (const bf16*)d_in[7];
  const bf16* dsk = (const bf16*)d_in[8];
  const bf16* wg  = (const bf16*)d_in[10];
  const bf16* wu  = (const bf16*)d_in[11];
  const bf16* wd  = (const bf16*)d_in[12];

  static EncFn enc = nullptr;
  static Scratch* S = nullptr;
  if (!enc) {
    void* fn = nullptr; cudaDriverEntryPointQueryResult qr;
    cudaGetDriverEntryPoint("cuTensorMapEncodeTiled", &fn, cudaEnableDefault, &qr);
    enc = (EncFn)fn;
    cudaGetSymbolAddress((void**)&S, g_scr);
    cudaFuncSetAttribute(k_all, cudaFuncAttributeMaxDynamicSharedMemorySize, M_TOTAL);
  }
  CUtensorMap tmA, tmG, tmU, tmD, tmLu, tmLx;
  {
    uint64_t dims[2] = {DM * 16, SEQ / 16}, st[1] = {DM * 32};
    uint32_t box[2] = {32, 128};
    make_map(enc, &tmLu, S->uT, 2, dims, st, box, CU_TENSOR_MAP_SWIZZLE_NONE);
    make_map(enc, &tmLx, S->xT, 2, dims, st, box, CU_TENSOR_MAP_SWIZZLE_NONE);
  }
  {
    uint64_t dims[3] = {64, DM, SEQ / 64}, st[2] = {SEQ * 2, 128};
    uint32_t box[3] = {64, 64, 1};
    make_map(enc, &tmA, S->hT, 3, dims, st, box, CU_TENSOR_MAP_SWIZZLE_128B);
  }
  {
    uint64_t dims[2] = {FF, DM}, st[1] = {FF * 2};
    uint32_t box[2] = {64, 64};
    make_map(enc, &tmG, wg, 2, dims, st, box, CU_TENSOR_MAP_SWIZZLE_128B);
    make_map(enc, &tmU, wu, 2, dims, st, box, CU_TENSOR_MAP_SWIZZLE_128B);
  }
  {
    uint64_t dims[2] = {DM, FF}, st[1] = {DM * 2};
    uint32_t box[2] = {64, 32};
    make_map(enc, &tmD, wd, 2, dims, st, box, CU_TENSOR_MAP_SWIZZLE_128B);
  }
  static_assert(FR_BAR == M_BAR + 320 && FR_BAR + 16 <= M_TOTAL, "barrier placement");
  static_assert(FRONT_SMEM <= M_XB, "front phase must not touch the MLP barriers");
  launch_k(k_all, 132, 512, M_TOTAL, false, S, Are, Aim, Bre, Bim, Cre, Cim, ldt, dsk, x, wg, wu, wd, tmLu, tmLx, tmA, tmG, tmU, tmD, (bf16*)d_out);
}
```
